```python
import torch

def _softmax(x, axis=-1):
    return torch.softmax(x, dim=axis)

def _gelu(x):
    return torch.nn.functional.gelu(x, approximate='tanh')

def _silu(x):
    return torch.nn.functional.silu(x)

def _sigmoid(x):
    return torch.sigmoid(x)

def _layernorm(x, axis=-1, eps=1e-05):
    m = x.mean(dim=axis, keepdim=True)
    v = x.var(dim=axis, keepdim=True, unbiased=False)
    return (x - m) / torch.sqrt(v + eps)

def _scatter_add(tgt, idx, src, axis=0):
    return tgt.clone().index_add_(axis, idx, src)

def _segment_sum(src, seg, n):
    out = torch.zeros((n,) + src.shape[1:], dtype=src.dtype)
    return out.index_add_(0, seg, src)

def _pad(x, pw):
    flat = tuple((v for pair in reversed(pw) for v in pair))
    return torch.nn.functional.pad(x, flat)
kernel_name = 'gated_mix__linear_kernel_hedgehog__memory_aug_recurrent_mem_tr__prompt'

def setup_inputs():

    _w = lambda a: (lambda t: t.to(torch.bfloat16) if t.is_floating_point() else t)(torch.as_tensor(a))

    def _A_setup():
        B, S, D, H = (1, 2048, 448, 16)
        Dh = D // H
        return {'x': _w((lambda *s: torch.randn(*s, dtype=torch.bfloat16) * 0.05)(B, S, D)), 'wqkv': _w((lambda *s: torch.randn(*s, dtype=torch.bfloat16) * 1.6)(D, 3 * D)), 'w_phi': _w((lambda *s: torch.randn(*s, dtype=torch.bfloat16) * 1.6)(H, Dh, Dh) * Dh ** (-0.5)), 'wo': _w((lambda *s: torch.randn(*s, dtype=torch.bfloat16) * 0.05)(D, D))}
    _A_in = _A_setup()

    def _B_setup():
        B, S, Dm = (1, 2048, 448)
        H, Dh = (16, 256)
        M, seg = (8, 32)
        seg = min(seg, S)
        S = S // seg * seg
        return {'x': _w((lambda *s: torch.randn(*s, dtype=torch.bfloat16) * 0.05)(B, S, Dm)), 'mem0': _w((lambda *s: torch.randn(*s, dtype=torch.bfloat16) * 0.8)(B, M, Dm)), 'Wq': _w((lambda *s: torch.randn(*s, dtype=torch.bfloat16) * 1.6)(Dm, H, Dh) * Dm ** (-0.5)), 'Wk': _w((lambda *s: torch.randn(*s, dtype=torch.bfloat16) * 1.6)(Dm, H, Dh) * Dm ** (-0.5)), 'Wv': _w((lambda *s: torch.randn(*s, dtype=torch.bfloat16) * 0.8)(Dm, H, Dh) * Dm ** (-0.5)), 'Wo': _w((lambda *s: torch.randn(*s, dtype=torch.bfloat16) * 0.8)(H, Dh, Dm) * (H * Dh) ** (-0.5)), 'seg_len': seg}
    _B_in = _B_setup()
    return {'A_x': _A_in['x'], 'A_wqkv': _A_in['wqkv'], 'A_w_phi': _A_in['w_phi'], 'A_wo': _A_in['wo'], 'B_x': _B_in['x'], 'B_mem0': _B_in['mem0'], 'B_Wq': _B_in['Wq'], 'B_Wk': _B_in['Wk'], 'B_Wv': _B_in['Wv'], 'B_Wo': _B_in['Wo'], 'B_seg_len': _B_in['seg_len'], 'gate_w': _w((lambda *s: torch.randn(*s, dtype=torch.bfloat16) * 0.05)(448) * 16.0)}

def reference(A_x, A_wqkv, A_w_phi, A_wo, B_x, B_mem0, B_Wq, B_Wk, B_Wv, B_Wo, B_seg_len, gate_w):

    def _A_ref(x, wqkv, w_phi, wo):
        B, S, D = x.shape
        H = 16
        Dh = D // H
        qkv = (lambda x, *d: x.permute(*d))((x @ wqkv).reshape(B, S, 3, H, Dh), 2, 0, 3, 1, 4)
        q, k, v = (qkv[0], qkv[1], qkv[2])
        pq = torch.einsum('bhsd,hdf->bhsf', q, w_phi)
        pk = torch.einsum('bhsd,hdf->bhsf', k, w_phi)
        phi_q = torch.concatenate([_softmax(pq, axis=-1), _softmax(-pq, axis=-1)], axis=-1)
        phi_k = torch.concatenate([_softmax(pk, axis=-1), _softmax(-pk, axis=-1)], axis=-1)
        kv = torch.einsum('bhsf,bhsd->bhfd', phi_k, v)
        z = torch.einsum('bhsf->bhf', phi_k)
        num = torch.einsum('bhqf,bhfd->bhqd', phi_q, kv)
        den = torch.einsum('bhqf,bhf->bhq', phi_q, z)[..., None] + 1e-06
        o = num / den
        return (lambda x, *d: x.permute(*d))(o, 0, 2, 1, 3).reshape(B, S, D) @ wo

    def _B_ref(x, mem0, Wq, Wk, Wv, Wo, seg_len):
        B, S, Dm = x.shape
        H, Dh = (Wq.shape[1], Wq.shape[2])
        M = mem0.shape[1]
        scale = Dh ** (-0.5)
        n_seg = S // seg_len
        L = M + seg_len
        idx = torch.arange(L)
        mask = (idx[:, None] < M) | (idx[:, None] >= idx[None, :])
        mem = mem0
        outs = []
        for s in range(n_seg):
            xs = x[:, s * seg_len:(s + 1) * seg_len, :].clone()
            h = torch.concatenate([mem, xs], axis=1)
            q = torch.einsum('btd,dhe->bhte', h, Wq)
            k = torch.einsum('btd,dhe->bhte', h, Wk)
            v = torch.einsum('btd,dhe->bhte', h, Wv)
            scores = torch.einsum('bhqe,bhke->bhqk', q, k) * scale
            scores = torch.where(mask[None, None], scores, -1000000000.0)
            p = _softmax(scores, axis=-1)
            o = torch.einsum('bhqk,bhke->bhqe', p, v)
            o = torch.einsum('bhte,hed->btd', o, Wo)
            mem = o[:, :M, :].clone()
            outs.append(o[:, M:, :])
        return torch.concatenate(outs, axis=1)
    x = A_x
    g = _sigmoid((x * gate_w).sum(-1, keepdims=True))
    a = _A_ref(x, A_wqkv, A_w_phi, A_wo)
    b = _B_ref(x, B_mem0, B_Wq, B_Wk, B_Wv, B_Wo, B_seg_len)
    return g * a + (1 - g) * b
```

```cpp
#include <cuda_runtime.h>
#include <cuda_bf16.h>
#include <cuda.h>
#include <stdint.h>

#define DBG_DUMP 0
#define PROFILE 0

#define EXP_NO_X 0
#define EXP_NO_BULK 0
#define TMA_AT 1
#define BULK_AT_E 1
#define RESET_EARLY 1
#define XM 15
#define GPRE 7
#define GFEN 0
#define PW_ROT 0
#define PW_N 5
#define PW_PF 0
#define PW_RST 1
#define PW_LAZY 0
#define NCOPY 1
#define HEXP 0
#define RETRY 0
#define GSW 4
#define PV_GAP 1
#define PV_AT -1
#define HDELAY 6000
#define HTHROT 1
typedef __nv_bfloat16 bf16;

constexpr int S_TOK = 2048, DM = 448, NH = 16, NSEG = 64;
constexpr uint32_t SENT = 0xFFFFFFFFu;

__device__ unsigned char g_XB[(2 << 20) + 17 * 65536];
__device__ unsigned int g_gbar;
__device__ __align__(256) unsigned char g_SXX[4 * 16 * 12544];
__device__ __align__(256) unsigned char g_PXG[4 * 16 * 2304];
__device__ unsigned int g_hbar;
__device__ __align__(16) float g_B[S_TOK * DM];
#define TL(i) do {} while (0)

__device__ __forceinline__ uint32_t smem_u32(const void* p) { return (uint32_t)__cvta_generic_to_shared(p); }
__device__ __forceinline__ uint32_t mapa(uint32_t a, uint32_t r) { uint32_t o; asm volatile("mapa.shared::cluster.u32 %0, %1, %2;" : "=r"(o) : "r"(a), "r"(r)); return o; }
__device__ __forceinline__ void mbar_init(uint32_t a, uint32_t c) { asm volatile("mbarrier.init.shared::cta.b64 [%0], %1;" ::"r"(a), "r"(c)); }
__device__ __forceinline__ void mbar_expect(uint32_t a, uint32_t b) { asm volatile("mbarrier.arrive.expect_tx.shared::cta.b64 _, [%0], %1;" ::"r"(a), "r"(b) : "memory"); }
__device__ __forceinline__ void mbar_arrive(uint32_t a) { asm volatile("mbarrier.arrive.shared::cta.b64 _, [%0];" ::"r"(a) : "memory"); }
__device__ __forceinline__ bool mbar_try(uint32_t a, uint32_t ph) {
    uint32_t p;
    asm volatile("{.reg .pred q; mbarrier.try_wait.parity.shared::cta.b64 q, [%1], %2; selp.u32 %0,1,0,q;}" : "=r"(p) : "r"(a), "r"(ph) : "memory");
    return p;
}
__device__ __forceinline__ void mbar_wait(uint32_t a, uint32_t ph, int& budget) {
    while (!mbar_try(a, ph) && ((--budget) & 0xffff) != 0) {}
}
__device__ __forceinline__ void cluster_sync() { asm volatile("barrier.cluster.arrive.aligned; barrier.cluster.wait.aligned;" ::: "memory"); }
template <int ID, int N> __device__ __forceinline__ void bar_sync() { asm volatile("bar.sync %0, %1;" ::"n"(ID), "n"(N) : "memory"); }
template <int ID, int N> __device__ __forceinline__ void bar_arrive() { asm volatile("bar.arrive %0, %1;" ::"n"(ID), "n"(N) : "memory"); }
__device__ __forceinline__ uint32_t clk() { uint32_t c; asm volatile("mov.u32 %0, %%clock;" : "=r"(c)::"memory"); return c; }
__device__ __forceinline__ uint32_t pack2(float lo, float hi) { uint32_t v; asm("cvt.rn.bf16x2.f32 %0, %1, %2;" : "=r"(v) : "f"(hi), "f"(lo)); return v; }
__device__ __forceinline__ float ex2(float x) { float y; asm("ex2.approx.ftz.f32 %0, %1;" : "=f"(y) : "f"(x)); return y; }
__device__ __forceinline__ float bf_lo(uint32_t v) { return __uint_as_float(v << 16); }
__device__ __forceinline__ float bf_hi(uint32_t v) { return __uint_as_float(v & 0xffff0000u); }

__device__ __forceinline__ void mma16(float* d, uint32_t a0, uint32_t a1, uint32_t a2, uint32_t a3, uint32_t b0, uint32_t b1) {
    asm volatile("mma.sync.aligned.m16n8k16.row.col.f32.bf16.bf16.f32 {%0,%1,%2,%3}, {%4,%5,%6,%7}, {%8,%9}, {%0,%1,%2,%3};"
                 : "+f"(d[0]), "+f"(d[1]), "+f"(d[2]), "+f"(d[3]) : "r"(a0), "r"(a1), "r"(a2), "r"(a3), "r"(b0), "r"(b1));
}
__device__ __forceinline__ void mma16z(float* d, uint32_t a0, uint32_t a1, uint32_t a2, uint32_t a3, uint32_t b0, uint32_t b1) {
    asm volatile("mma.sync.aligned.m16n8k16.row.col.f32.bf16.bf16.f32 {%0,%1,%2,%3}, {%4,%5,%6,%7}, {%8,%9}, {%10,%10,%10,%10};"
                 : "=f"(d[0]), "=f"(d[1]), "=f"(d[2]), "=f"(d[3]) : "r"(a0), "r"(a1), "r"(a2), "r"(a3), "r"(b0), "r"(b1), "f"(0.f));
}
__device__ __forceinline__ void mma8z(float* d, uint32_t a0, uint32_t a1, uint32_t b0) {
    asm volatile("mma.sync.aligned.m16n8k8.row.col.f32.bf16.bf16.f32 {%0,%1,%2,%3}, {%4,%5}, {%6}, {%7,%7,%7,%7};"
                 : "=f"(d[0]), "=f"(d[1]), "=f"(d[2]), "=f"(d[3]) : "r"(a0), "r"(a1), "r"(b0), "f"(0.f));
}
__device__ __forceinline__ void mma8(float* d, uint32_t a0, uint32_t a1, uint32_t b0) {
    asm volatile("mma.sync.aligned.m16n8k8.row.col.f32.bf16.bf16.f32 {%0,%1,%2,%3}, {%4,%5}, {%6}, {%0,%1,%2,%3};"
                 : "+f"(d[0]), "+f"(d[1]), "+f"(d[2]), "+f"(d[3]) : "r"(a0), "r"(a1), "r"(b0));
}
__device__ __forceinline__ float rcp(float x) { float y; asm("rcp.approx.ftz.f32 %0, %1;" : "=f"(y) : "f"(x)); return y; }
__device__ __forceinline__ void ldsm4t(uint32_t* r, uint32_t a) {
    asm volatile("ldmatrix.sync.aligned.m8n8.x4.trans.shared.b16 {%0,%1,%2,%3}, [%4];" : "=r"(r[0]), "=r"(r[1]), "=r"(r[2]), "=r"(r[3]) : "r"(a) : "memory");
}
__device__ __forceinline__ void ldsm4(uint32_t* r, uint32_t a) {
    asm volatile("ldmatrix.sync.aligned.m8n8.x4.shared.b16 {%0,%1,%2,%3}, [%4];" : "=r"(r[0]), "=r"(r[1]), "=r"(r[2]), "=r"(r[3]) : "r"(a) : "memory");
}
__device__ __forceinline__ void stsm4(uint32_t a, uint32_t r0, uint32_t r1, uint32_t r2, uint32_t r3) {
    asm volatile("stmatrix.sync.aligned.m8n8.x4.shared.b16 [%0], {%1,%2,%3,%4};" ::"r"(a), "r"(r0), "r"(r1), "r"(r2), "r"(r3) : "memory");
}
__device__ __forceinline__ void sts32(uint32_t a, uint32_t v) { asm volatile("st.shared.u32 [%0], %1;" ::"r"(a), "r"(v) : "memory"); }
__device__ __forceinline__ void sts64(uint32_t a, uint32_t x, uint32_t y) { asm volatile("st.shared.v2.u32 [%0], {%1,%2};" ::"r"(a), "r"(x), "r"(y) : "memory"); }
__device__ __forceinline__ void sts128(uint32_t a, uint32_t x, uint32_t y, uint32_t z, uint32_t w) { asm volatile("st.shared.v4.u32 [%0], {%1,%2,%3,%4};" ::"r"(a), "r"(x), "r"(y), "r"(z), "r"(w) : "memory"); }
__device__ __forceinline__ uint32_t lds32(uint32_t a) { uint32_t v; asm volatile("ld.shared.u32 %0, [%1];" : "=r"(v) : "r"(a) : "memory"); return v; }
__device__ __forceinline__ void lds64(uint32_t* r, uint32_t a) { asm volatile("ld.shared.v2.u32 {%0,%1}, [%2];" : "=r"(r[0]), "=r"(r[1]) : "r"(a) : "memory"); }
__device__ __forceinline__ void lds128(uint32_t* r, uint32_t a) { asm volatile("ld.shared.v4.u32 {%0,%1,%2,%3}, [%4];" : "=r"(r[0]), "=r"(r[1]), "=r"(r[2]), "=r"(r[3]) : "r"(a) : "memory"); }
__device__ __forceinline__ void stg32(void* p, uint32_t v) { asm volatile("st.relaxed.gpu.global.u32 [%0], %1;" ::"l"(p), "r"(v) : "memory"); }
__device__ __forceinline__ void stg64(void* p, uint32_t v, uint32_t w) { asm volatile("st.relaxed.gpu.global.v2.u32 [%0], {%1,%2};" ::"l"(p), "r"(v), "r"(w) : "memory"); }
__device__ __forceinline__ void stg128(void* p, uint32_t x, uint32_t y, uint32_t z, uint32_t w) { asm volatile("st.relaxed.gpu.global.v4.u32 [%0], {%1,%2,%3,%4};" ::"l"(p), "r"(x), "r"(y), "r"(z), "r"(w) : "memory"); }
__device__ __forceinline__ void ldg64(uint32_t* r, const void* p) { asm volatile("ld.relaxed.gpu.global.v2.u32 {%0,%1}, [%2];" : "=r"(r[0]), "=r"(r[1]) : "l"(p) : "memory"); }
__device__ __forceinline__ void ldg128(uint32_t* r, const void* p) { asm volatile("ld.relaxed.gpu.global.v4.u32 {%0,%1,%2,%3}, [%4];" : "=r"(r[0]), "=r"(r[1]), "=r"(r[2]), "=r"(r[3]) : "l"(p) : "memory"); }
__device__ __forceinline__ void stg128a(void* p, uint32_t x, uint32_t y, uint32_t z, uint32_t w) {
    asm volatile("{.reg .b128 v; .reg .b64 lo, hi; mov.b64 lo, {%1,%2}; mov.b64 hi, {%3,%4}; mov.b128 v, {lo, hi}; st.relaxed.gpu.global.b128 [%0], v;}" ::"l"(p), "r"(x), "r"(y), "r"(z), "r"(w) : "memory");
}
__device__ __forceinline__ void ldg128a(uint32_t* r, const void* p) {
    asm volatile("{.reg .b128 v; .reg .b64 lo, hi; ld.relaxed.gpu.global.b128 v, [%4]; mov.b128 {lo, hi}, v; mov.b64 {%0,%1}, lo; mov.b64 {%2,%3}, hi;}" : "=r"(r[0]), "=r"(r[1]), "=r"(r[2]), "=r"(r[3]) : "l"(p) : "memory");
}
__device__ __forceinline__ void stg64a(void* p, uint32_t x, uint32_t y) {
    asm volatile("{.reg .b64 v; mov.b64 v, {%1,%2}; st.relaxed.gpu.global.b64 [%0], v;}" ::"l"(p), "r"(x), "r"(y) : "memory");
}
__device__ __forceinline__ void ldg64a(uint32_t* r, const void* p) {
    asm volatile("{.reg .b64 v; ld.relaxed.gpu.global.b64 v, [%2]; mov.b64 {%0,%1}, v;}" : "=r"(r[0]), "=r"(r[1]) : "l"(p) : "memory");
}
__device__ __forceinline__ void stas64(uint32_t a, float x, float y, uint32_t bar) {
    asm volatile("st.async.shared::cluster.mbarrier::complete_tx::bytes.v2.f32 [%0], {%1,%2}, [%3];" ::"r"(a), "f"(x), "f"(y), "r"(bar) : "memory");
}
__device__ __forceinline__ void stas64u(uint32_t a, uint32_t x, uint32_t y, uint32_t bar) {
    asm volatile("st.async.shared::cluster.mbarrier::complete_tx::bytes.v2.u32 [%0], {%1,%2}, [%3];" ::"r"(a), "r"(x), "r"(y), "r"(bar) : "memory");
}
__device__ __forceinline__ void stas128(uint32_t a, uint32_t x, uint32_t y, uint32_t z, uint32_t w, uint32_t bar) {
    asm volatile("st.async.shared::cluster.mbarrier::complete_tx::bytes.v4.u32 [%0], {%1,%2,%3,%4}, [%5];" ::"r"(a), "r"(x), "r"(y), "r"(z), "r"(w), "r"(bar) : "memory");
}
__device__ __forceinline__ void stas128f(uint32_t a, float x, float y, float z, float w, uint32_t bar) {
    asm volatile("st.async.shared::cluster.mbarrier::complete_tx::bytes.v4.f32 [%0], {%1,%2,%3,%4}, [%5];" ::"r"(a), "f"(x), "f"(y), "f"(z), "f"(w), "r"(bar) : "memory");
}
__device__ __forceinline__ void tma2d(uint32_t dst, const CUtensorMap* tm, int c0, int c1, uint32_t bar) {
    asm volatile("cp.async.bulk.tensor.2d.shared::cluster.global.mbarrier::complete_tx::bytes [%0], [%1, {%3, %4}], [%2];"
                 ::"r"(dst), "l"(tm), "r"(bar), "r"(c0), "r"(c1) : "memory");
}
__device__ __forceinline__ void tma2d_mc(uint32_t dst, const CUtensorMap* tm, int c0, int c1, uint32_t bar, uint16_t mask) {
    asm volatile("cp.async.bulk.tensor.2d.shared::cluster.global.mbarrier::complete_tx::bytes.multicast::cluster [%0], [%1, {%3, %4}], [%2], %5;"
                 ::"r"(dst), "l"(tm), "r"(bar), "r"(c0), "r"(c1), "h"(mask) : "memory");
}
#define WG_FENCE() asm volatile("wgmma.fence.sync.aligned;" ::: "memory")
#define WG_COMMIT() asm volatile("wgmma.commit_group.sync.aligned;" ::: "memory")
#define WG_WAIT0() asm volatile("wgmma.wait_group.sync.aligned 0;" ::: "memory")
__device__ __forceinline__ uint64_t desc_sw128(uint32_t addr) {
    return (uint64_t)((addr & 0x3FFFF) >> 4) | ((uint64_t)1 << 16) | ((uint64_t)64 << 32) | ((uint64_t)1 << 62);
}
__device__ __forceinline__ void wg_n32_rs(float* d, const uint32_t* a, uint32_t dlo, int sc, uint32_t dhi) {
    asm volatile("{.reg .pred p; .reg .b64 dd; setp.ne.b32 p, %21, 0; mov.b64 dd, {%20, %22};\n\t"
                 "wgmma.mma_async.sync.aligned.m64n32k16.f32.bf16.bf16 {%0,%1,%2,%3,%4,%5,%6,%7,%8,%9,%10,%11,%12,%13,%14,%15}, {%16,%17,%18,%19}, dd, p, 1, 1, 0;}"
                 : "+f"(d[0]), "+f"(d[1]), "+f"(d[2]), "+f"(d[3]), "+f"(d[4]), "+f"(d[5]), "+f"(d[6]), "+f"(d[7]), "+f"(d[8]), "+f"(d[9]), "+f"(d[10]), "+f"(d[11]), "+f"(d[12]), "+f"(d[13]), "+f"(d[14]), "+f"(d[15])
                 : "r"(a[0]), "r"(a[1]), "r"(a[2]), "r"(a[3]), "r"(dlo), "r"(sc), "r"(dhi));
}
__device__ __forceinline__ void wg_n40_rs(float* d, const uint32_t* a, uint32_t dlo, int sc, uint32_t dhi) {
    asm volatile("{.reg .pred p; .reg .b64 dd; setp.ne.b32 p, %25, 0; mov.b64 dd, {%24, %26};\n\t"
                 "wgmma.mma_async.sync.aligned.m64n40k16.f32.bf16.bf16 {%0,%1,%2,%3,%4,%5,%6,%7,%8,%9,%10,%11,%12,%13,%14,%15,%16,%17,%18,%19}, {%20,%21,%22,%23}, dd, p, 1, 1, 0;}"
                 : "+f"(d[0]), "+f"(d[1]), "+f"(d[2]), "+f"(d[3]), "+f"(d[4]), "+f"(d[5]), "+f"(d[6]), "+f"(d[7]), "+f"(d[8]), "+f"(d[9]), "+f"(d[10]), "+f"(d[11]), "+f"(d[12]), "+f"(d[13]), "+f"(d[14]), "+f"(d[15]), "+f"(d[16]), "+f"(d[17]), "+f"(d[18]), "+f"(d[19])
                 : "r"(a[0]), "r"(a[1]), "r"(a[2]), "r"(a[3]), "r"(dlo), "r"(sc), "r"(dhi));
}
template <int TA>
__device__ __forceinline__ void wg_n64_ss(float* d, uint64_t da, uint64_t db, int sc) {
    asm volatile("{.reg .pred p; setp.ne.b32 p, %34, 0;\n\t"
                 "wgmma.mma_async.sync.aligned.m64n64k16.f32.bf16.bf16 {%0,%1,%2,%3,%4,%5,%6,%7,%8,%9,%10,%11,%12,%13,%14,%15,%16,%17,%18,%19,%20,%21,%22,%23,%24,%25,%26,%27,%28,%29,%30,%31}, %32, %33, p, 1, 1, %35, 0;}"
                 : "+f"(d[0]), "+f"(d[1]), "+f"(d[2]), "+f"(d[3]), "+f"(d[4]), "+f"(d[5]), "+f"(d[6]), "+f"(d[7]), "+f"(d[8]), "+f"(d[9]), "+f"(d[10]), "+f"(d[11]), "+f"(d[12]), "+f"(d[13]), "+f"(d[14]), "+f"(d[15]), "+f"(d[16]), "+f"(d[17]), "+f"(d[18]), "+f"(d[19]), "+f"(d[20]), "+f"(d[21]), "+f"(d[22]), "+f"(d[23]), "+f"(d[24]), "+f"(d[25]), "+f"(d[26]), "+f"(d[27]), "+f"(d[28]), "+f"(d[29]), "+f"(d[30]), "+f"(d[31])
                 : "l"(da), "l"(db), "r"(sc), "n"(TA));
}

constexpr int PW_STAGE = 8192, PW_NST = PW_N;
template <int MAT>
__device__ __forceinline__ void make_weights(uint32_t* W, uint32_t sA, uint32_t sB, uint32_t barA, uint32_t barF, uint32_t barE, int& budget) {
    const float sc = MAT == 0 ? 0.0625f * 1.4426950408889634f : 1.0f;
    int st = 0, ph = 0;
#pragma unroll
    for (int q = 0; q < 7; q++) {
        float acc[32];
#pragma unroll 1
        for (int kb = 0; kb < 4; kb++) {
            if (q == 0) mbar_wait(barA + kb * 8, 0, budget);
            mbar_wait(barF + st * 8, ph, budget);
            const uint64_t da = desc_sw128(sA + kb * 8192), db = desc_sw128(sB + st * PW_STAGE);
            WG_FENCE();
#pragma unroll
            for (int k = 0; k < 4; k++) wg_n64_ss<MAT>(acc, da + k * (MAT ? 128 : 2), db + k * 2, kb + k > 0);
            WG_COMMIT();
            WG_WAIT0();
            if ((threadIdx.x & 127) == 0) mbar_arrive(barE + st * 8);
            if (++st == PW_NST) { st = 0; ph ^= 1; }
        }
#pragma unroll
        for (int i = 0; i < 16; i++) W[q * 16 + i] = pack2(acc[2 * i] * sc, acc[2 * i + 1] * sc);
    }
}

constexpr int XT = 5120, XSLOT = 7 * XT;
constexpr int SM_X = 0;
constexpr int SM_KX = 4 * XSLOT;
constexpr int SM_ZU = SM_KX + 4 * 4096;
constexpr int SM_XRED = SM_ZU + 4 * 4096;
constexpr int SM_KM = SM_XRED + 4 * 4096;
constexpr int SM_ZR = SM_KM + 1024;
constexpr int SM_RED = SM_ZR + 4 * 1024;
constexpr int SM_PX = SM_RED + 2048;
constexpr int PW_XS = PW_NST <= 3 ? 3 : (PW_NST <= 5 ? 2 : 1);
constexpr int SM_QB = 3 * XSLOT + 65536 + 6 * PW_STAGE;
constexpr int SM_PB = SM_PX + 3584;
static_assert(SM_PB + 2 * 2304 <= SM_QB, "smem layout");
constexpr int SM_BAR = SM_QB + 1024;
constexpr int SM_NEAR = SM_BAR + 512;
constexpr int SM_PROF = SM_PB + 2 * 2304;
constexpr int MAIN_SMEM = 1024 + SM_NEAR + 128;

constexpr int BAR_A = 1, BAR_B = 2, BAR_B2 = 3, BAR_D = 4, BAR_E = 5, BAR_H = 6, BAR_P = 7, BAR_E0 = 8, BAR_J1 = 9, BAR_J2 = 10, BAR_J3 = 11,
              BAR_G = 12, BAR_F = 13, BAR_T = 14, BAR_G2 = 15;
constexpr int CNT_A = 256 + 64, CNT_B = 128 + 32, CNT_B2 = 128 + 32, CNT_D = 128 + 32, CNT_E = 128 + 32, CNT_H = 256 + 64, CNT_P = 128 + 64, CNT_T = BULK_AT_E ? 288 : 256;
constexpr int SXX_SLOT = 16 * 12544, PXG_SLOT = 16 * 2304;
constexpr int SMM_SLOT = 16384, SMX_SLOT = 16384;

__device__ __forceinline__ uint32_t gtime() { uint32_t t; asm volatile("mov.u32 %0, %%globaltimer_lo;" : "=r"(t)::"memory"); return t; }
#define PROF(idx) do {} while (0)
#define PROFG(idx) do {} while (0)
#define SCHED_FENCE() asm volatile("{.reg .pred p; setp.eq.u32 p, %0, %1; @p trap;}" ::"r"(zero), "n"(__LINE__) : "memory")
__device__ __forceinline__ uint32_t keep(uint32_t x) { return __shfl_sync(0xffffffffu, x, threadIdx.x & 31); }
__device__ __forceinline__ float keep(float x) { return __shfl_sync(0xffffffffu, x, threadIdx.x & 31); }
template <class T> __device__ __forceinline__ T* keep(T* x) { return (T*)__shfl_sync(0xffffffffu, (unsigned long long)x, threadIdx.x & 31); }
__device__ __forceinline__ uint32_t xor_or(uint32_t a, uint32_t t, uint32_t acc) { uint32_t r; asm("lop3.b32 %0, %1, %2, %3, 0xBE;" : "=r"(r) : "r"(a), "r"(t), "r"(acc)); return r; }

__device__ __forceinline__ void delay_cycles(int n, uint32_t z) {
#pragma unroll 1
    for (int i = 0; i < n; i++)
        asm volatile("mul.lo.u32 %0, %0, %0;\n\tmul.lo.u32 %0, %0, %0;\n\tmul.lo.u32 %0, %0, %0;\n\tmul.lo.u32 %0, %0, %0;" : "+r"(z)::"memory");
    asm volatile("{.reg .pred p; setp.eq.u32 p, %0, 12345; @p trap;}" ::"r"(z) : "memory");
}
__device__ __forceinline__ void wait_until(uint32_t t, int lane) {
    asm volatile("{.reg .pred p, z; .reg .u32 n;\n\t"
                 "setp.ge.s32 z, %1, 0;\n\t"
                 "WU_LOOP:\n\t"
                 "@z mov.u32 n, %%globaltimer_lo;\n\t"
                 "sub.u32 n, %0, n;\n\t"
                 "setp.lt.u32 p, n, 4096;\n\t"
                 "@p bra WU_LOOP;}" ::"r"(t - 1), "r"(lane) : "memory");
}

__device__ __forceinline__ int probe_near(unsigned char* pair, int sub) {
    int votes = 0;
#pragma unroll 1
    for (int r = 0; r < 6 && abs(votes) < 2; r++) {
        int dt[2];
#pragma unroll
        for (int c = 0; c < 2; c++) {
            unsigned* p = (unsigned*)(pair + c * 4096 + 2048 + sub * 128);
            const uint32_t t0 = clk();
            unsigned x = atomicAdd(p, 1);
            while (x == 0xdeadbeefu) x = atomicAdd(p, 1);
            dt[c] = (int)(clk() - t0);
        }
        if (min(dt[0], dt[1]) < 400 && abs(dt[0] - dt[1]) > 90) votes += dt[1] < dt[0] ? 1 : -1;
    }
    return votes > 0;
}

__device__ __forceinline__ void ldg64x7(uint32_t (*v)[2], const void* p) {
    asm volatile("ld.relaxed.gpu.global.v2.u32 {%0,%1}, [%14];\n\tld.relaxed.gpu.global.v2.u32 {%2,%3}, [%14+256];\n\t"
                 "ld.relaxed.gpu.global.v2.u32 {%4,%5}, [%14+512];\n\tld.relaxed.gpu.global.v2.u32 {%6,%7}, [%14+768];\n\t"
                 "ld.relaxed.gpu.global.v2.u32 {%8,%9}, [%14+1024];\n\tld.relaxed.gpu.global.v2.u32 {%10,%11}, [%14+1280];\n\t"
                 "ld.relaxed.gpu.global.v2.u32 {%12,%13}, [%14+1536];"
                 : "=r"(v[0][0]), "=r"(v[0][1]), "=r"(v[1][0]), "=r"(v[1][1]), "=r"(v[2][0]), "=r"(v[2][1]), "=r"(v[3][0]), "=r"(v[3][1]),
                   "=r"(v[4][0]), "=r"(v[4][1]), "=r"(v[5][0]), "=r"(v[5][1]), "=r"(v[6][0]), "=r"(v[6][1])
                 : "l"(p) : "memory");
}
template <int N>
__device__ __forceinline__ bool any_sent7(uint32_t (*v)[N]) {
    uint32_t m = 0;
#pragma unroll
    for (int k = 0; k < 7; k++)
#pragma unroll
        for (int i = 0; i < N; i++) m = max(m, v[k][i]);
    return __any_sync(0xffffffffu, m == SENT);
}
template <int N>
__device__ __forceinline__ float sum7(uint32_t (*v)[N], int i) {
    return ((__uint_as_float(v[0][i]) + __uint_as_float(v[1][i])) + (__uint_as_float(v[2][i]) + __uint_as_float(v[3][i]))) +
           ((__uint_as_float(v[4][i]) + __uint_as_float(v[5][i])) + __uint_as_float(v[6][i]));
}

__device__ __forceinline__ void ldg64ax7(uint32_t (*v)[2], const unsigned char* p) {
#pragma unroll
    for (int k = 0; k < 7; k++) ldg64a(v[k], p + k * 256);
}
__device__ __forceinline__ uint32_t ldg32(const void* p) { uint32_t v; asm volatile("ld.relaxed.gpu.global.u32 %0, [%1];" : "=r"(v) : "l"(p) : "memory"); return v; }

__device__ __forceinline__ void xhalf(int HF, int s, uint32_t sb, uint32_t kx0, unsigned char* gbase, uint32_t j256, uint32_t l16, uint32_t pxa, int lane, uint32_t tpoll, int& budget) {
    const int sl = s & 3;
    const uint32_t kxa = kx0 + sl * 4096;
    uint32_t kx[2][8];
#pragma unroll
    for (int nt = 0; nt < 2; nt++) { ldsm4t(&kx[nt][0], kxa + nt * 1024); ldsm4t(&kx[nt][4], kxa + nt * 1024 + 512); }
    unsigned char* base = gbase + sl * SMX_SLOT;
    const unsigned char* rx = base + (lds32(sb + SM_NEAR + 4) ^ 4096);
    const uint32_t tag = (s >> 2) & 1;
    if (s > 0) mbar_wait(sb + SM_BAR + 40, (s - 1) & 1, budget);
    uint32_t qa[8];
    lds128(&qa[0], l16 + SM_QB);
    lds128(&qa[4], l16 + SM_QB + 512);
    float s1[2][4], s2[2][4];
#pragma unroll
    for (int nt = 0; nt < 2; nt++) {
        mma16z(s1[nt], qa[0], qa[1], qa[2], qa[3], kx[nt][0], kx[nt][1]);
        mma16z(s2[nt], qa[0], qa[1], qa[2], qa[3], kx[nt][2], kx[nt][3]);
    }
#pragma unroll
    for (int nt = 0; nt < 2; nt++) {
        mma16(s1[nt], qa[4], qa[5], qa[6], qa[7], kx[nt][4], kx[nt][5]);
        mma16(s2[nt], qa[4], qa[5], qa[6], qa[7], kx[nt][6], kx[nt][7]);
    }
    const uint32_t w0 = (__byte_perm(pack2(s1[0][0] + s2[0][2], 0.f), __float_as_uint(s1[0][1] + s2[0][3]), 0x7610) & ~1u) | tag;
    const uint32_t w1 = __byte_perm(pack2(s1[1][0] + s2[1][2], 0.f), __float_as_uint(s1[1][1] + s2[1][3]), 0x7610);
    stg64a(base + j256, w0, w1);
    stg64a(base + j256 + 4096, w0, w1);
    if (!HF) PROF(5);
    wait_until(tpoll, lane);
    if (!HF) PROF(19);
    uint32_t xa[7][2];
    while (true) {
        ldg64ax7(xa, rx);
        uint32_t x0 = 0;
#pragma unroll
        for (int k = 0; k < 7; k++) x0 = xor_or(xa[k][0], tag, x0);
        if (!__any_sync(0xffffffffu, x0 & 1) || (budget -= 65536) <= 0) break;
    }
    float t[4];
#pragma unroll
    for (int nt = 0; nt < 2; nt++) {
        t[2 * nt] = ((bf_lo(xa[0][nt]) + bf_lo(xa[1][nt])) + (bf_lo(xa[2][nt]) + bf_lo(xa[3][nt]))) + ((bf_lo(xa[4][nt]) + bf_lo(xa[5][nt])) + bf_lo(xa[6][nt]));
        t[2 * nt + 1] = sum7<2>(xa, nt);
    }
    float mx = fmaxf(fmaxf(t[0], t[1]), fmaxf(t[2], t[3]));
    if (!HF) PROF(13);
    mx = fmaxf(mx, __shfl_xor_sync(0xffffffffu, mx, 1));
    mx = fmaxf(mx, __shfl_xor_sync(0xffffffffu, mx, 2));
#pragma unroll
    for (int i = 0; i < 4; i++) t[i] = ex2(t[i] - mx);
    sts64(l16 + SM_PX + 2560 + HF * 8, __float_as_uint(mx), __float_as_uint((t[0] + t[1]) + (t[2] + t[3])));
    bar_arrive<BAR_J1, 96>();
    const uint32_t p0 = pack2(t[0], t[1]), p1 = pack2(t[2], t[3]);
    sts128(pxa, p0, 0u, 0u, p0);
    sts128(pxa + 512, p1, 0u, 0u, p1);
    bar_arrive<BAR_J2, 192>();
    if (!HF) PROF(3);
}

__device__ __forceinline__ void g_role(uint32_t sb, uint32_t h, uint32_t j, int lane, int tf, int& budget) {
    const int g = lane >> 2, q = lane & 3;
    const uint32_t idb = keep(pack2(g == 2 * q ? 1.f : 0.f, g == 2 * q + 1 ? 1.f : 0.f));
    const float NI = -INFINITY, d0 = 2 * q <= g ? 0.f : NI, d1 = 2 * q + 1 <= g ? 0.f : NI;
    const float b2 = keep(j > 0 ? 0.f : d0), b3 = keep(j > 0 ? 0.f : d1), b4 = keep(j >= 2 ? 0.f : NI);
    const float b6 = keep(j == 3 ? 0.f : (j == 2 ? d0 : NI)), b7 = keep(j == 3 ? 0.f : (j == 2 ? d1 : NI));
    const float b8 = keep((j & 1) ? d0 : NI), b9 = keep((j & 1) ? d1 : NI);
    uint32_t v0[7][2] = {}, v1[7][2] = {}, vq[8] = {};
    const unsigned char* r0 = keep(g_SXX + h * 12544 + j * 1792 + lane * 8);
    const unsigned char* r2 = keep(g_SXX + h * 12544 + 10752 + (j >> 1) * 896 + lane * 4);
    unsigned char* pg16 = keep(g_PXG + h * 2304 + lane * 16);
    unsigned char* pg4 = keep(g_PXG + h * 2304 + 2048 + lane * 4);
    const uint32_t pa16 = keep(sb + SM_PB + lane * 16), pa8 = keep(sb + SM_PB + 2048 + lane * 8);
#pragma unroll 1
    for (int s = 0; s < NSEG + 2; s++) {
        const bool own = s > 0 && s <= NSEG && j < 4 && !EXP_NO_X && (XM & 2);
        const uint32_t tag = ((s - 1) >> 2) & 1, so = ((s - 1) & 3) * SXX_SLOT;
        if (s < NSEG) wait_until(lds32(sb + SM_NEAR + 96 + ((s - 1) & 1) * 4) + tf, lane);
        bool first = true;
        while (true) {
            if (own) {
                ldg64ax7(v0, r0 + so);
                if (j >= 2) ldg64ax7(v1, r0 + so + 3584);
                if (j & 1) {
#pragma unroll
                    for (int k = 0; k < 7; k++) vq[k] = ldg32(r2 + so + k * 128);
                }
            }
            if (first) {
                if (s >= 2 && !EXP_NO_X && (XM & 4)) {
                    const uint32_t po = ((s - 2) & 3) * PXG_SLOT, tg2 = ((s - 2) >> 2) & 1;
                    uint32_t v[4][4], m2, m3, x;
                    do {
#pragma unroll
                        for (int k = 0; k < 4; k++) ldg128a(v[k], pg16 + po + k * 512);
                        m2 = ldg32(pg4 + po);
                        m3 = ldg32(pg4 + po + 128);
                        x = xor_or(v[0][3], tg2, xor_or(v[1][3], tg2, xor_or(v[2][3], tg2, xor_or(v[3][3], tg2, xor_or(m2, tg2, m3 ^ tg2)))));
                    } while (__any_sync(0xffffffffu, x & 1) && (XM & 7) == 7 && (budget -= 65536) > 0);
#pragma unroll
                    for (int k = 0; k < 4; k++) sts128(pa16 + (s & 1) * 2304 + k * 512, v[k][0], v[k][1], v[k][2], v[k][3]);
                    sts64(pa8 + (s & 1) * 2304, m2, m3);
                }
                if (s <= NSEG) bar_arrive<BAR_D, CNT_D>(); else bar_arrive<BAR_G2, CNT_D>();
                first = false;
            }
            if (!own) break;
            uint32_t x0 = 0, x1 = 0, x2 = 0;
#pragma unroll
            for (int k = 0; k < 7; k++) { x0 = xor_or(v0[k][0], tag, x0); x1 = xor_or(v1[k][0], tag, x1); x2 = xor_or(vq[k], tag, x2); }
            if (!__any_sync(0xffffffffu, (x0 | (x1 & (j >> 1)) | (x2 & j)) & 1) || (XM & 3) != 3 || (budget -= 65536) <= 0) break;
        }
        if (s < NSEG) bar_sync<BAR_H, CNT_H>();
        if (s + 1 < NSEG) bar_arrive<BAR_A, CNT_A>();
        if (own) {
            float t0[4] = {0.f, 0.f, b2, b3}, t1[4] = {b4, b4, b6, b7}, tq[4] = {b8, b9, 0.f, 0.f};
            mma16(t0, v0[0][0], v0[0][1], v0[1][0], v0[1][1], idb, idb);
            mma16(t1, v1[0][0], v1[0][1], v1[1][0], v1[1][1], idb, idb);
            mma16(tq, vq[0], vq[1], vq[2], vq[3], idb, idb);
            mma16(t0, v0[2][0], v0[2][1], v0[3][0], v0[3][1], idb, idb);
            mma16(t1, v1[2][0], v1[2][1], v1[3][0], v1[3][1], idb, idb);
            mma16(tq, vq[4], vq[5], vq[6], vq[7], idb, idb);
            mma16(t0, v0[4][0], v0[4][1], v0[5][0], v0[5][1], idb, idb);
            mma16(t1, v1[4][0], v1[4][1], v1[5][0], v1[5][1], idb, idb);
            mma8(t0, v0[6][0], v0[6][1], idb);
            mma8(t1, v1[6][0], v1[6][1], idb);
            float e[10] = {t0[0], t0[1], t0[2], t0[3], t1[0], t1[1], t1[2], t1[3], tq[0] + tq[2], tq[1] + tq[3]};
            float mx = e[0];
#pragma unroll
            for (int i = 1; i < 10; i++) mx = fmaxf(mx, e[i]);
            mx = fmaxf(mx, __shfl_xor_sync(0xffffffffu, mx, 1));
            mx = fmaxf(mx, __shfl_xor_sync(0xffffffffu, mx, 2));
            float l = 0.f;
#pragma unroll
            for (int i = 0; i < 10; i++) { e[i] = ex2(e[i] - mx); l += e[i]; }
            l += __shfl_xor_sync(0xffffffffu, l, 1);
            l += __shfl_xor_sync(0xffffffffu, l, 2);
            const float inv = rcp(l);
            uint32_t pb[5];
#pragma unroll
            for (int i = 0; i < 5; i++) pb[i] = pack2(e[2 * i] * inv, e[2 * i + 1] * inv);
            const uint32_t po = ((s - 1) & 3) * PXG_SLOT;
            stg128a(pg16 + po + j * 512, pb[1], j < 2 ? pb[4] : pb[2], j < 2 ? pb[0] : pb[3], (pb[4] & ~1u) | tag);
            if (j >= 2) stg32(pg4 + po + (j - 2) * 128, (pb[0] & ~1u) | tag);
        }
        if (s < NSEG) PROF(12);
    }
}

template <bool B> struct Flag { static constexpr bool v = B; };
#define RUN_STEPS(S0, LO, HI, S1, body) do { _Pragma("unroll 1") for (int s_ = (S0); s_ < (S1); s_++) body(s_, Flag<false>()); } while (0)

__global__ void __launch_bounds__(384, 1)
k_main(const __grid_constant__ CUtensorMap tmX, const __grid_constant__ CUtensorMap tmWq, const __grid_constant__ CUtensorMap tmWk,
       const __grid_constant__ CUtensorMap tmWv, const __grid_constant__ CUtensorMap tmWo, const bf16* __restrict__ xin, const bf16* __restrict__ mem0,
       const bf16* __restrict__ wq, const bf16* __restrict__ wk, const bf16* __restrict__ wv, const bf16* __restrict__ wo, int c1, int d3, int cx, int thr, int extra, int dxf, int dpv, int dtx, int hold, uint32_t zero) {
    extern __shared__ unsigned char smraw[];
    const uint32_t sb = (smem_u32(smraw) + 1023) & ~1023u;
    uint32_t h, j;
    asm volatile("mov.u32 %0, %%cluster_ctarank;" : "=r"(h));
    asm volatile("mov.u32 %0, %%clusterid.x;" : "=r"(j));
    const int tid = threadIdx.x, lane = tid & 31;
    const int g = lane >> 2, q = lane & 3;
    const uint32_t barX = sb + SM_BAR, barR = barX + 32, barQ = barX + 40, barXR = barX + 48;
    const uint32_t anchor_addr = sb + SM_NEAR + 96;
    int budget = 1 << 28;
    unsigned char* const g_MEMX = (unsigned char*)(((uintptr_t)g_XB + 0x1fffff) & ~(uintptr_t)0x1fffff);
    unsigned char* const g_SM = g_MEMX + 65536;
    constexpr int TLB = 0;
    TL(0);
    asm volatile("griddepcontrol.launch_dependents;");
    if (PW_PF && tid < 16) {
        const bf16* src = (tid & 3) == 0 ? wk : ((tid & 3) == 1 ? wv : ((tid & 3) == 2 ? wq : wo));
        asm volatile("cp.async.bulk.prefetch.L2.global [%0], %1;" ::"l"(src + (size_t)((tid >> 2) * 112 + blockIdx.x) * 4096), "r"(8192) : "memory");
    }
    const uint32_t pwA = sb + PW_XS * XSLOT, pwB = pwA + 65536, barPA = barX + 80, barPF = barPA + 64, barPE = barPF + 144;
    if (tid == 0) {
        for (int i = 0; i < 54; i++) mbar_init(barX + i * 8, 1);
        asm volatile("fence.mbarrier_init.release.cluster;" ::: "memory");
        for (int i = 0; i < 3; i++) mbar_expect(barX + i * 8, 28672);
        mbar_expect(barR, 2048);
        mbar_expect(barQ, 1024);
        for (int i = 0; i < 4; i++) mbar_expect(barXR + i * 8, 4096);
        sts64(anchor_addr, gtime() - 100000, gtime() - 100000);
        sts64(sb + SM_NEAR, 0, 0);
    }
    __syncthreads();
    asm volatile("barrier.cluster.arrive.aligned;" ::: "memory");
    uint32_t W[112];
    const int wg0 = __shfl_sync(0xffffffffu, tid >> 7, 0);
    if (wg0 < 2) {

        if (wg0 == 0) make_weights<0>(W, pwA, pwB, barPA, barPF, barPE, budget);
        else make_weights<1>(W, pwA + 32768, pwB + PW_NST * PW_STAGE, barPA + 32, barPF + 72, barPE + 72, budget);
        TL(1);
        asm volatile("barrier.cluster.wait.aligned;" ::: "memory");
    } else {
        const int warp = 8 + __shfl_sync(0xffffffffu, (tid >> 5) & 3, 0);
#pragma unroll
        for (int i = 0; i < 112; i++) W[i] = 0;
        if (warp < 10) {
            const int m = warp - 8;
            if (lane < 4) {
                mbar_expect(barPA + m * 32 + lane * 8, 8192);
                if (m == 0) tma2d(pwA + lane * 8192, &tmWq, h * 256 + lane * 64, j * 64, barPA + lane * 8);
                else tma2d(pwA + 32768 + lane * 8192, &tmWo, j * 64, h * 256 + lane * 64, barPA + 32 + lane * 8);
            }
            __syncwarp();
            int st = 0, ph = 1;
#pragma unroll 1
            for (int it = 0; it < 28; it++) {
                mbar_wait(barPE + m * 72 + st * 8, ph, budget);
                if (lane == 0) {
                    mbar_expect(barPF + m * 72 + st * 8, PW_STAGE);
                    tma2d(pwB + (m * PW_NST + st) * PW_STAGE, m == 0 ? &tmWk : &tmWv, h * 256 + (it & 3) * 64, (((it >> 2) + PW_ROT * j) % 7) * 64, barPF + m * 72 + st * 8);
                }
                __syncwarp();
                if (++st == PW_NST) { st = 0; ph ^= 1; }
            }
            asm volatile("barrier.cluster.wait.aligned;" ::: "memory");

        } else {

            const int u = tid - 320;
            asm volatile("barrier.cluster.wait.aligned;" ::: "memory");
            if (u == 32) {
                if (h < 7) { for (int i = 0; i < PW_XS; i++) tma2d_mc(sb + SM_X + i * XSLOT + h * XT + 1024, &tmX, h * 64, i * 32, barX + i * 8, 0xFFFF); }
                if (blockIdx.x < 64) asm volatile("cp.async.bulk.prefetch.L2.global [%0], %1;" ::"l"(xin + (size_t)blockIdx.x * 32 * DM), "r"(32 * DM * 2) : "memory");
            }
            __syncwarp();
            const uint32_t* m0 = (const uint32_t*)(mem0 + ((u >> 2) & 7) * DM + j * 64 + (u >> 5) * 32 + (u & 3) * 2);
            sts128(sb + SM_QB + u * 16, m0[0], m0[4], m0[8], m0[12]);
            const int gw = blockIdx.x * 64 + u;
            for (int i = gw; i < 4 * 16384 / 16; i += 112 * 64) stg128(g_MEMX + i * 16, SENT, SENT, SENT, SENT);
            for (int i = gw; i < 16 * 65536 / 16; i += 112 * 64) { if ((i & 255) < (((i & 512) || !(i & 3072)) ? 224 : 112)) stg128(g_SM + i * 16, SENT, SENT, SENT, SENT); }
            for (int i = gw; i < 4 * SXX_SLOT / 16; i += 112 * 64) stg128(g_SXX + i * 16, SENT, SENT, SENT, SENT);
            for (int i = gw; i < 4 * PXG_SLOT / 16; i += 112 * 64) stg128(g_PXG + i * 16, SENT, SENT, SENT, SENT);
            __threadfence();
            bar_sync<BAR_F, 64>();
            if (u == 0) {
                const unsigned gen = atomicAdd(&g_gbar, 1) / 112 + 1, target = gen * 112;
                sts32(sb + SM_NEAR + 64, gen & 1);
                for (int i = 0; i < (1 << 20); i++) {
                    unsigned v;
                    asm volatile("ld.acquire.gpu.global.u32 %0, [%1];" : "=r"(v) : "l"(&g_gbar) : "memory");
                    if ((int)(v - target) >= 0) break;
                }
            }
            __syncwarp();
        }
    }
    __syncthreads();
    asm volatile("barrier.cluster.arrive.aligned;" ::: "memory");
    TL(2);
    budget = 1 << 28;
    const int warp = __shfl_sync(0xffffffffu, tid >> 5, 0);
    const uint32_t l16 = keep(sb + lane * 16), l8 = keep(sb + lane * 8);

    if (warp < 8) {
        asm volatile("setmaxnreg.inc.sync.aligned.u32 192;");
        const int wg = warp >> 2, w = warp & 3, t = tid & 127;
        if (wg == 0) {
            const uint32_t ktw = keep(sb + SM_KX + (2 * w + ((lane >> 3) & 1)) * 128 + (lane >> 4) * 1024 + (lane & 7) * 16);
            float acc[16];
            auto bulk_issue = [&](int sg) {
                const uint32_t dlo = (((sb + SM_X + (sg & 3) * XSLOT + 1024) & 0x3FFFF) >> 4) | (1u << 16);
                WG_FENCE();
#pragma unroll
                for (int k = 0; k < 28; k++) wg_n32_rs(acc, &W[4 * k], dlo + (k >> 2) * (XT / 16) + (k & 3) * 2, k > 0, 0x40000040u + zero);
                WG_COMMIT();
            };
            auto bulk_store = [&](int sg) {
                WG_WAIT0();
                const uint32_t kt = ktw + (sg & 3) * 4096;
                stsm4(kt, pack2(acc[0], acc[1]), pack2(acc[2], acc[3]), pack2(acc[4], acc[5]), pack2(acc[6], acc[7]));
                stsm4(kt + 2048, pack2(acc[8], acc[9]), pack2(acc[10], acc[11]), pack2(acc[12], acc[13]), pack2(acc[14], acc[15]));
            };
            unsigned char* ws = keep(g_SXX + h * 12544 + (w < 3 ? w * 3584 + j * 256 + lane * 8 : 10752 + j * 128 + lane * 4));
            const int arow = (lane & 7) + (w == 3 ? 8 + 16 * ((lane >> 3) & 1) : (w == 0 ? 0 : 16) + 8 * ((lane >> 3) & 1));
            const uint32_t xoff = keep(sb + SM_X + j * XT + 1024 + arow * 128 + (((lane >> 4) ^ (arow & 7)) << 4));
            const uint32_t oaddr = keep(sb + SM_KM + w * 256 + lane * 4);
            uint32_t ma = sb + SM_X + XSLOT + (lane & 7) * 128 + (((lane >> 3) ^ (lane & 7)) << 4);
            auto step = [&](int s, auto fl) {
                constexpr bool ST = decltype(fl)::v;
                if (s >= 0) {
                {
                    const uint32_t mb = ma ^ 64;
                    bar_sync<BAR_A, CNT_A>();
                    float ac[4][4];
                    uint32_t b[14][4];
#pragma unroll
                    for (int kk = 6; kk < 14; kk++) { ldsm4(b[kk], ((kk & 1) ? mb : ma) + (kk >> 1) * XT); if (kk == 6 && warp == 0) PROF(0); }
#pragma unroll
                    for (int k3 = 0; k3 < 14; k3++) {
                        const int kk = (k3 + 6) % 14, c0 = (2 * kk) & 3, c1i = (2 * kk + 1) & 3;
                        if (k3 == GSW) {
                            bar_sync<BAR_F, 256>();
#pragma unroll
                            for (int k4 = 0; k4 < 6; k4++) ldsm4(b[k4], ((k4 & 1) ? mb : ma) + (k4 >> 1) * XT);
                        }
                        if (k3 < 2) {
                            mma16z(ac[c0], W[8 * kk], W[8 * kk + 1], W[8 * kk + 2], W[8 * kk + 3], b[kk][0], b[kk][1]);
                            mma16z(ac[c1i], W[8 * kk + 4], W[8 * kk + 5], W[8 * kk + 6], W[8 * kk + 7], b[kk][2], b[kk][3]);
                        } else {
                            mma16(ac[c0], W[8 * kk], W[8 * kk + 1], W[8 * kk + 2], W[8 * kk + 3], b[kk][0], b[kk][1]);
                            mma16(ac[c1i], W[8 * kk + 4], W[8 * kk + 5], W[8 * kk + 6], W[8 * kk + 7], b[kk][2], b[kk][3]);
                        }
                    }
                    sts32(oaddr, pack2((ac[0][0] + ac[1][0]) + (ac[2][0] + ac[3][0]), (ac[0][1] + ac[1][1]) + (ac[2][1] + ac[3][1])));
                    sts32(oaddr + 128, pack2((ac[0][2] + ac[1][2]) + (ac[2][2] + ac[3][2]), (ac[0][3] + ac[1][3]) + (ac[2][3] + ac[3][3])));
                    bar_arrive<BAR_B, CNT_B>();
                    SCHED_FENCE();
                    if (warp == 0) PROF(1);
                    if (ST || s > 0) {
                        const uint32_t t3 = lds32(anchor_addr + ((s - 1) & 1) * 4);
                        if (w == 0 && (ST || s + 2 < NSEG)) {
                            wait_until(t3 + dtx, lane);
                            if (lane == 0) {
                                const int sg = s + 2;
                                mbar_expect(barX + (sg & 3) * 8, 28672);
                                if (h < 7) tma2d_mc(sb + SM_X + (sg & 3) * XSLOT + h * XT + 1024, &tmX, h * 64, sg * 32, barX + (sg & 3) * 8, 0xFFFF);
                            }
                            __syncwarp();
                        }
                    }
                }
                const bool dosc = !EXP_NO_X && (XM & 1);
                uint32_t a[4][4], b0[8], b1[8];
                bar_sync<BAR_H, CNT_H>();
                if (dosc) {
                    const uint32_t xa = (s & 3) * XSLOT + xoff;
#pragma unroll
                    for (int k = 0; k < 4; k++) ldsm4(a[k], xa ^ (k * 32));
                    const uint32_t kxa = l16 + SM_KX + (s & 3) * 4096;
                    const uint32_t kt0 = w < 2 ? l16 + SM_KM : kxa + 1024, kt1 = w < 2 ? kxa : kxa + w * 1024;
                    ldsm4t(&b0[0], kt0); ldsm4t(&b0[4], kt0 + 512);
                    ldsm4t(&b1[0], kt1); ldsm4t(&b1[4], kt1 + 512);
                }
                uint32_t w0, w1, w2, w3;
                if (dosc) {
                    float sa[2][4], sc2[2][4];
                    mma16z(sa[0], a[0][0], a[0][1], a[0][2], a[0][3], b0[0], b0[1]);
                    mma16z(sa[1], a[1][0], a[1][1], a[1][2], a[1][3], b0[2], b0[3]);
                    mma16z(sc2[0], a[0][0], a[0][1], a[0][2], a[0][3], b1[0], b1[1]);
                    mma16z(sc2[1], a[1][0], a[1][1], a[1][2], a[1][3], b1[2], b1[3]);
                    mma16(sa[0], a[2][0], a[2][1], a[2][2], a[2][3], b0[4], b0[5]);
                    mma16(sa[1], a[3][0], a[3][1], a[3][2], a[3][3], b0[6], b0[7]);
                    mma16(sc2[0], a[2][0], a[2][1], a[2][2], a[2][3], b1[4], b1[5]);
                    mma16(sc2[1], a[3][0], a[3][1], a[3][2], a[3][3], b1[6], b1[7]);
                    w0 = pack2(sa[0][0] + sa[1][0], sa[0][1] + sa[1][1]); w1 = pack2(sa[0][2] + sa[1][2], sa[0][3] + sa[1][3]);
                    w2 = pack2(sc2[0][0] + sc2[1][0], sc2[0][1] + sc2[1][1]); w3 = pack2(sc2[0][2] + sc2[1][2], sc2[0][3] + sc2[1][3]);
                    unsigned char* wp = ws + (s & 3) * SXX_SLOT;
                    const uint32_t tag = (s >> 2) & 1;
                    if (w < 3) {
                        stg64a(wp, (w0 & ~1u) | tag, w2);
                        stg64a(wp + 1792, (w1 & ~1u) | tag, w3);
                    } else {
                        stg32(wp, (w0 & ~1u) | tag);
                        stg32(wp + 896, (w3 & ~1u) | tag);
                    }
                    if (warp == 0 && (ST || s < NSEG)) PROF(22);
                }
                ma += XSLOT;
                if (ma >= sb + SM_X + 4 * XSLOT) ma -= 4 * XSLOT;
                }
                if (ST || s + 2 < NSEG) mbar_wait(barX + ((s + 2) & 3) * 8, ((s + 2) >> 2) & 1, budget);
                if (s >= 0 && s + 1 < NSEG) bar_sync<BAR_T, CNT_T>();
                if (ST || s + 2 < NSEG) { bulk_issue(s + 2); bulk_store(s + 2); }
                if (s == -1) { bar_arrive<BAR_P, CNT_P>(); asm volatile("barrier.cluster.wait.aligned;" ::: "memory"); TL(3); }
                if (w == 0 && s >= 0) PROF(2);
            };
            RUN_STEPS(-2, 1, NSEG - 2, NSEG, step);
        } else {
            uint32_t so0;
            { const int i = (t >> 3) & 7; so0 = sb + SM_X + XSLOT + (t >> 6) * XT + i * 128 + (((t & 7) ^ i) << 4); }
#pragma unroll
            for (int k = 0; k < 4; k++) {
                const int kb = k == 0 ? 0 : (k == 1 ? 2 : (k == 2 ? 3 : 5));
                if (k != 1 || w < 2) {
                    const uint4 v = *(const uint4*)(mem0 + ((t >> 3) & 7) * DM + ((t >> 6) + kb) * 64 + (t & 7) * 8);
                    sts128(so0 + kb * XT, v.x, v.y, v.z, v.w);
                }
            }
            const uint32_t dd = keep(mapa(sb + SM_RED + h * 128 + (w & 1) * 64 + q * 16, (w >> 1) * 8 + g)), rr = keep(mapa(barR, (w >> 1) * 8 + g));
            const uint32_t laddr = keep(sb + SM_PX + 3072 + g * 16), xaddr = l8 + SM_PX + 3200;
            const unsigned char *p0 = g_MEMX, *p1 = g_MEMX;
            const uint32_t lim = keep(w < 2 ? 2048u : 2816u + w * 128 - t * 16), msk = keep(w < 2 ? 0xffffffffu : 0u);
            uint32_t uc[8];
            const uint32_t pvd = keep(mapa(sb + SM_XRED + h * 256 + ((w ^ h) & 3) * 64 + g * 8, q)), pvb = keep(mapa(barXR, q));
            const uint32_t rank4 = keep(mapa(sb, 4) - mapa(sb, 0));
            const uint32_t zua = keep(l16 + SM_ZU + w * 1024), zra = keep(l8 + SM_ZR + w * 256);
            const unsigned char* pb0 = keep(g_MEMX + t * 16);
            uint32_t ov[4][2] = {};
            auto send_pv = [&](int sg) {
                if (EXP_NO_X || !(XM & 8)) return;
                const uint32_t bo = sg & 3;
#pragma unroll
                for (int nb = 0; nb < 4; nb++) stas64u(pvd + bo * 4096 + nb * rank4, ov[nb][0], ov[nb][1], pvb + bo * 8 + nb * rank4);
            };
            auto do_pv = [&](int s) {
                if (EXP_NO_X || !(XM & 8)) return;
                const uint32_t bo = (s - 2) & 3, pa = SM_PB + (s & 1) * 2304;
                uint32_t zr[2], zu[8], pq[4][4], pmk[2];
                lds128(&zu[0], zua + bo * 4096);
#pragma unroll
                for (int nb = 0; nb < 4; nb++) lds128(pq[nb], l16 + pa + nb * 512);
                lds64(zr, zra + bo * 1024);
                lds64(pmk, l8 + pa + 2048);
                lds128(&zu[4], zua + bo * 4096 + 512);
                float c[4][4];
#pragma unroll
                for (int nb = 0; nb < 4; nb++) mma16z(c[nb], zu[0], zu[1], zu[2], zu[3], pq[nb][0], pq[nb][1]);
#pragma unroll
                for (int nb = 0; nb < 4; nb++) mma8(c[nb], zr[0], zr[1], nb < 2 ? pq[nb][2] : pmk[nb - 2]);
#pragma unroll
                for (int nb = 2; nb < 4; nb++) mma16(c[nb], zu[4], zu[5], zu[6], zu[7], pq[nb][2], pq[nb][3]);
#pragma unroll
                for (int nb = 0; nb < 4; nb++) { ov[nb][0] = pack2(c[nb][0], c[nb][1]); ov[nb][1] = pack2(c[nb][2], c[nb][3]); }
            };
            auto step = [&](int s, auto fl) {
                constexpr bool ST = decltype(fl)::v;
                const int sg = s + 1;
                if (ST || s > 0) {
                    const uint32_t t3 = lds32(anchor_addr + ((s - 1) & 1) * 4);
                    bar_sync<BAR_E, CNT_E>();
                    wait_until(t3, lane);
                    if (warp == 4) PROF(15);
                    uint32_t a[4][4] = {}, m;
                    ldg128(a[0], p1);
                    ldg128(a[1], p1 + 2048);
                    ldg128(a[2], p0);
                    ldg128(a[3], p0 + lim);
                    while (true) {
                        sts128(so0 + 3 * XT, a[0][0], a[0][1], a[0][2], a[0][3]);
                        sts128(so0 + 5 * XT, a[1][0], a[1][1], a[1][2], a[1][3]);
                        m = max(max(max(a[0][0], a[0][1]), max(a[0][2], a[0][3])), max(max(a[1][0], a[1][1]), max(a[1][2], a[1][3])));
                        if (!__any_sync(0xffffffffu, m == SENT) || (budget -= 65536) <= 0) break;
                        ldg128(a[0], p1);
                        ldg128(a[1], p1 + 2048);
                    }
                    bar_arrive<BAR_A, CNT_A>();
                    while (true) {
                        sts128(so0, a[2][0], a[2][1], a[2][2], a[2][3]);
                        if (w < 2) sts128(so0 + 2 * XT, a[3][0], a[3][1], a[3][2], a[3][3]);
                        m = max(max(max(a[2][0], a[2][1]), max(a[2][2], a[2][3])), msk & max(max(a[3][0], a[3][1]), max(a[3][2], a[3][3])));
                        if (!__any_sync(0xffffffffu, m == SENT) || (budget -= 65536) <= 0) break;
                        ldg128(a[2], p0);
                        ldg128(a[3], p0 + lim);
                    }
                    bar_arrive<BAR_F, 256>();
                }
                if (warp == 4 && (ST || s >= 0)) PROF(17);
                if (PV_AT < 0 && s >= 3) { wait_until(lds32(anchor_addr + ((s - 1) & 1) * 4) + dpv, lane); send_pv(s - 3); }
                if (ST || sg < NSEG) mbar_wait(barX + (sg & 3) * 8, (sg >> 2) & 1, budget);
                float acc[20];
                const uint32_t dlo = (((sb + SM_X + (sg & 3) * XSLOT) & 0x3FFFF) >> 4) | (1u << 16);
                const uint32_t pva = pvd + ((s - 3) & 3) * 4096, pvc = pvb + ((s - 3) & 3) * 8;
                asm volatile("fence.proxy.async.shared::cta;" ::: "memory");
                WG_FENCE();
                if (ST || s >= 0) bar_sync<BAR_B2, CNT_B2>();
#pragma unroll
                for (int k = 0; k < 28; k++) {
                    wg_n40_rs(acc, &W[4 * k], dlo + (k >> 2) * (XT / 16) + (k & 3) * 2, k > 0, 0x40000040u + zero);
                    if (PV_AT >= 0 && k >= PV_AT && k < PV_AT + 4 * PV_GAP && (k - PV_AT) % PV_GAP == 0) {
                        const int nb = (k - PV_AT) / PV_GAP;
                        asm volatile("{.reg .pred p; setp.ge.s32 p, %4, 3; @p st.async.shared::cluster.mbarrier::complete_tx::bytes.v2.u32 [%0], {%1,%2}, [%3];}"
                                     ::"r"(pva + nb * rank4), "r"(ov[nb][0]), "r"(ov[nb][1]), "r"(pvc + nb * rank4), "r"(s) : "memory");
                    }
                }
                WG_COMMIT();
                uint32_t r0, r1;
                if (s >= 0 && sg < NSEG) {
                    uint32_t px[4][4];
                    bar_sync<BAR_J2, 192>();
#pragma unroll
                    for (int nt = 0; nt < 4; nt++) lds128(px[nt], l16 + SM_PX + nt * 512);
                    WG_WAIT0();
                    if (warp == 4) PROF(14);
                    float o[4], o2[4];
                    mma16z(o, px[0][0], px[0][1], px[0][2], px[0][3], uc[0], uc[1]);
                    mma16z(o2, px[2][0], px[2][1], px[2][2], px[2][3], uc[4], uc[5]);
                    mma16(o, px[1][0], px[1][1], px[1][2], px[1][3], uc[2], uc[3]);
                    mma16(o2, px[3][0], px[3][1], px[3][2], px[3][3], uc[6], uc[7]);
                    r0 = pack2(acc[0], acc[1]); r1 = pack2(acc[2], acc[3]);
                    bar_sync<BAR_J3, 160>();
                    uint32_t pq[4], la[4], axs[2];
                    lds128(pq, l16 + SM_PX + 2048);
                    lds64(axs, xaddr);
                    lds128(la, laddr);
                    float om[4];
                    mma16z(om, pq[0], pq[1], pq[2], pq[3], r0, r1);
#pragma unroll
                    for (int i = 0; i < 4; i++) o[i] = fmaf(o[i], __uint_as_float(axs[0]), o2[i] * __uint_as_float(axs[1]));
                    const float inv = rcp((__uint_as_float(la[0]) + __uint_as_float(la[1])) + (__uint_as_float(la[2]) + __uint_as_float(la[3])));
#pragma unroll
                    for (int i = 0; i < 4; i++) o[i] *= inv;
                    stas128f(dd, fmaf(om[0], inv, o[0]), fmaf(om[1], inv, o[1]), fmaf(om[2], inv, o[2]), fmaf(om[3], inv, o[3]), rr);
                    if (warp == 4) PROF(9);
                } else {
                    WG_WAIT0();
                    r0 = pack2(acc[0], acc[1]); r1 = pack2(acc[2], acc[3]);
                    if (s < 0) asm volatile("barrier.cluster.wait.aligned;" ::: "memory");
                }
                if (s >= 0) { bar_sync<BAR_D, CNT_D>(); bar_arrive<BAR_H, CNT_H>(); }
#pragma unroll
                for (int i = 0; i < 8; i++) uc[i] = pack2(acc[4 + 2 * i], acc[5 + 2 * i]);
                if (ST || s >= 0) sts64(zra + (s & 3) * 1024, r0, r1);
                if (ST || sg < NSEG) {
                    const uint32_t zu = zua + (sg & 3) * 4096;
                    sts128(zu, uc[0], uc[1], uc[2], uc[3]);
                    sts128(zu + 512, uc[4], uc[5], uc[6], uc[7]);
                }
                if (ST || s >= 2) do_pv(s);
                if (ST || (s >= 0 && sg < NSEG)) asm volatile("bar.arrive %0, %1;" ::"r"(BAR_T + (ov[3][1] & zero)), "n"(CNT_T) : "memory");
                if (warp == 4 && (ST || s >= 0)) PROF(24);
                if (ST || s >= 0) {
                    const int sl = s & 3;
                    const uint32_t nm = lds32(sb + SM_NEAR);
                    p0 = pb0 + (sl * 16384 + nm);
                    p1 = pb0 + (sl * 16384 + 12288 - nm);
                    const int dq = (sl == 2) ? -3 * XSLOT : XSLOT;
                    so0 += dq;
                }
            };
            bar_arrive<BAR_A, CNT_A>();
            bar_arrive<BAR_F, 256>();
            RUN_STEPS(-1, 3, NSEG - 1, NSEG, step);
#pragma unroll 1
            for (int s = NSEG; s < NSEG + 3; s++) {
                send_pv(s - 3);
                if (s == NSEG + 2) break;
                if (s == NSEG) bar_sync<BAR_D, CNT_D>(); else bar_sync<BAR_G2, CNT_D>();
                do_pv(s);
            }
        }
    } else {
      asm volatile("setmaxnreg.dec.sync.aligned.u32 120;");
      asm volatile("barrier.cluster.wait.aligned;" ::: "memory");
      if (tid == 352 && h < 7) { for (int i = PW_XS; i < 3; i++) tma2d_mc(sb + SM_X + i * XSLOT + h * XT + 1024, &tmX, h * 64, i * 32, barX + i * 8, 0xFFFF); }
      __syncwarp();
      if (warp >= 10) bar_arrive<BAR_A, CNT_A>();
      const int mi = lane >> 3;
      const uint32_t lperm = keep(sb + ((((mi & 1) << 1) | (mi >> 1)) * 128) + (lane & 7) * 16);
      if (warp == 8) {
        unsigned char* wbase = keep(g_SM + h * 65536 + j * 256 + lane * 8);
        const unsigned char* rbase = keep(g_SM + h * 65536 + lane * 8);
        const unsigned char* tbase = keep(g_MEMX + 3584 + (lane & 7) * 32);
        unsigned char* wp = wbase;
        const unsigned char* rm = rbase;
        uint32_t anchor = lds32(anchor_addr), t3 = anchor;
        int ok = 0, alt = 0, undo = 0, retry = RETRY ? -1 : 0;
        auto step = [&](int s, auto fl) {
            constexpr bool ST = decltype(fl)::v;
            if (ST || s > 0) {
                const int sp = (s - 1) & 3;
                const unsigned char* tp = tbase + (sp * 16384 + lds32(sb + SM_NEAR));
                bar_sync<BAR_E0, 64>();
                wait_until(t3, lane);
                uint32_t ts;
                int tries = 64;
                do { ts = ldg32(tp); } while (__any_sync(0xffffffffu, lane < 7 && ts == SENT) && --tries > 0);
                const uint32_t t0 = __shfl_sync(0xffffffffu, ts, 0) - 0x100000u;
                const uint32_t tmx = __reduce_max_sync(0xffffffffu, lane < 7 ? ts - t0 : 0u) + t0;
                const int late = (int)(tmx + thr - t3);
                if (late <= 0) {
                    anchor = t3 + c1;
                    if (++ok == 10 && undo) { c1 -= undo & 32; d3 -= undo >> 8; undo = 0; ok = 1; }
                } else {
                    anchor = tmx + extra;
                    if (ok > 0 && ok < hold && s > 4) { if (late > 160 && (alt ^= 1)) { c1 += 32; undo = retry & 32; } else { d3 += 32; undo = retry & 8192; } retry = 0; }
                    ok = 0;
                }
                t3 = anchor + d3;
                if (lane == 0) sts32(anchor_addr + (s & 1) * 4, t3);
                rm += lds32(sb + SM_NEAR + 4);
                mbar_wait(barQ, (s - 1) & 1, budget);
            }
            uint32_t qa[8];
            lds128(&qa[0], l16 + SM_QB);
            lds128(&qa[4], l16 + SM_QB + 512);
            if (s + 1 == NSEG) { bar_sync<BAR_B, CNT_B>(); bar_arrive<BAR_B2, CNT_B2>(); return; }
            bar_sync<BAR_B, CNT_B>();
            {
                uint32_t km[8];
                ldsm4t(&km[0], lperm + SM_KM);
                ldsm4t(&km[4], lperm + SM_KM + 512);
                float s1[4], s2[4], s3[4], s4[4];
                mma16z(s1, qa[0], qa[1], qa[2], qa[3], km[0], km[1]);
                mma16z(s2, qa[0], qa[1], qa[2], qa[3], km[2], km[3]);
                mma16z(s3, qa[4], qa[5], qa[6], qa[7], km[4], km[5]);
                mma16z(s4, qa[4], qa[5], qa[6], qa[7], km[6], km[7]);
                bar_arrive<BAR_B2, CNT_B2>();
                const float sm0 = (s1[0] + s2[2]) + (s3[0] + s4[2]), sm1 = (s1[1] + s2[3]) + (s3[1] + s4[3]);
                stg64(wp, __float_as_uint(sm0), __float_as_uint(sm1));
                stg64(wp + 4096, __float_as_uint(sm0), __float_as_uint(sm1));
            }
            PROF(6);
            wait_until(anchor, lane);
            uint32_t pm[7][2];
            ldg64x7(pm, rm);
            bar_sync<BAR_J1, 96>();
            uint32_t st[4];
            lds128(st, l16 + SM_PX + 2560);
            const float mx0 = __uint_as_float(st[0]), lx0 = __uint_as_float(st[1]), mx1 = __uint_as_float(st[2]), lx1 = __uint_as_float(st[3]);
            const float mx = fmaxf(mx0, mx1);
            while (true) {
                float e0 = sum7<2>(pm, 0), e1 = sum7<2>(pm, 1);
                const float chk = e0 + e1;
                float mn = fmaxf(fmaxf(e0, e1), mx);
                mn = fmaxf(mn, __shfl_xor_sync(0xffffffffu, mn, 1));
                mn = fmaxf(mn, __shfl_xor_sync(0xffffffffu, mn, 2));
                e0 = ex2(e0 - mn);
                e1 = ex2(e1 - mn);
                const float ax0 = ex2(mx0 - mn), ax1 = ex2(mx1 - mn);
                const uint32_t pmm = pack2(e0, e1);
                sts128(l16 + SM_PX + 2048, pmm, 0u, 0u, pmm);
                sts64(l8 + SM_PX + 3200, __float_as_uint(ax0), __float_as_uint(ax1));
                sts32(sb + SM_PX + 3072 + lane * 4, __float_as_uint(fmaf(ax0, lx0, fmaf(ax1, lx1, e0 + e1))));
                if (!__any_sync(0xffffffffu, chk != chk)) break;
                if (!any_sent7<2>(pm) || (budget -= 65536) <= 0) break;
                ldg64x7(pm, rm);
            }
            bar_arrive<BAR_J3, 160>();
            PROF(21);
            {
                unsigned char* wr = wbase + ((s + 2) & 3) * SMM_SLOT;
                stg64(wr, SENT, SENT); stg64(wr + 4096, SENT, SENT);
            }
            const int sl = (s + 1) & 3;
            wp = wbase + sl * SMM_SLOT;
            rm = rbase + sl * SMM_SLOT;
        };
        RUN_STEPS(0, 2, NSEG - 1, NSEG, step);
      } else if (warp < 11) {
        const int moffs = j * 1024 + (h & 7) * 128 + (h >> 3) * 64, pair = moffs >= 3072;
        unsigned char* wp3 = keep(g_MEMX + pair * 8192 + (lane >> 4) * 4096 + (moffs - pair * 3072) + (lane & 15) * 4);
        unsigned char* wts = keep(g_MEMX + (lane >> 4) * 4096 + 3584 + j * 32 + (lane & 7) * 4);
        const bool tsw = h == 0 && (lane & 15) < 8;
        const uint32_t ra = keep(sb + SM_RED + (lane >> 4) * 1024 + ((lane >> 3) & 1) * 64 + (lane & 3) * 16 + ((lane >> 2) & 1) * 8);
        const uint32_t qd0 = keep(mapa(sb + SM_QB + (h >> 3) * 512 + (h & 7) * 64 + q * 16, g)), qb0 = keep(mapa(barQ, g));
        const uint32_t rank8 = keep(mapa(sb, 8) - mapa(sb, 0));
        uint32_t sel[4];
#pragma unroll
        for (int m = 0; m < 4; m++) sel[m] = keep(g == 2 * m ? 0x00003f80u : (g == 2 * m + 1 ? 0x3f800000u : 0u));
        float* ob = keep(g_B + (size_t)(2 * h) * DM + j * 64 + 16 * q + g);
        const uint32_t kx0 = keep(lperm + SM_KX + (warp - 9) * 2048), pxa = keep(l16 + SM_PX + (warp - 9) * 1024);
        unsigned char* gsm = keep(g_SM + h * 65536 + 8192 + (warp - 9) * 1792 + lane * 8);
        const uint32_t par = lds32(sb + SM_NEAR + 64);
        const uint32_t xr0 = keep(sb + SM_XRED + q * 256 + q * 64 + g * 8);
        bar_sync<BAR_P, CNT_P>();
        unsigned char *wps = wp3, *wtl = wts;
#pragma unroll 1
        for (int s = 0; s < NSEG + 3; s++) {
            if (s + 1 < NSEG) xhalf(warp - 9, s, sb, kx0, gsm, j * 256, l16, pxa, lane, lds32(anchor_addr + ((s - 1) & 1) * 4) + cx, budget);
            if (warp == 10) {
                const int sg = s - 3;
                if (s < NSEG) bar_sync<BAR_H, CNT_H>();
                if (sg >= 0 && !EXP_NO_X && (XM & 8)) {
                    const uint32_t bo = sg & 3;
                    uint32_t v[4][2][4];
                    mbar_wait(barXR + bo * 8, (sg >> 2) & 1, budget);
#pragma unroll
                    for (int m = 0; m < 4; m++)
#pragma unroll
                        for (int u = 0; u < 4; u++) lds64(&v[m][u >> 1][2 * (u & 1)], ((xr0 + bo * 4096) ^ (m * 64)) + u * 1024);
                    float c0[4], c1[4];
                    mma16z(c0, v[0][0][0], v[0][0][1], v[0][0][2], v[0][0][3], sel[0], sel[0]);
                    mma16z(c1, v[0][1][0], v[0][1][1], v[0][1][2], v[0][1][3], sel[0], sel[0]);
#pragma unroll
                    for (int m = 1; m < 4; m++) {
                        mma16(c0, v[m][0][0], v[m][0][1], v[m][0][2], v[m][0][3], sel[m], sel[m]);
                        mma16(c1, v[m][1][0], v[m][1][1], v[m][1][2], v[m][1][3], sel[m], sel[m]);
                    }
                    float* o = ob + (size_t)sg * 32 * DM;
                    o[0] = __uint_as_float((__float_as_uint(c0[0] + c1[0]) & ~1u) | par); o[DM] = __uint_as_float((__float_as_uint(c0[1] + c1[1]) & ~1u) | par);
                    o[8] = __uint_as_float((__float_as_uint(c0[2] + c1[2]) & ~1u) | par); o[DM + 8] = __uint_as_float((__float_as_uint(c0[3] + c1[3]) & ~1u) | par);
                    if (lane == 0) mbar_expect(barXR + bo * 8, 4096);
                    __syncwarp();
                }
                if (s + 1 < NSEG) bar_arrive<BAR_A, CNT_A>();
                if (s < NSEG) PROF(25);
                continue;
            }
            if (s + 1 >= NSEG) break;
            stg32(wp3 + ((s + 2) & 3) * 16384, SENT);
            if (tsw) stg32(wts + ((s + 2) & 3) * 16384, SENT);
            if (lane == 0 && s > 0) mbar_expect(barQ, 1024);
            __syncwarp();
            mbar_wait(barR, s & 1, budget);
            uint32_t v[8][2];
#pragma unroll
            for (int k = 0; k < 8; k++) lds64(v[k], ra + k * 128);
            if (tsw) stg32(wtl, gtime() & ~1u);
            PROF(10);
            float sx = ((__uint_as_float(v[0][0]) + __uint_as_float(v[1][0])) + (__uint_as_float(v[2][0]) + __uint_as_float(v[3][0]))) +
                       ((__uint_as_float(v[4][0]) + __uint_as_float(v[5][0])) + (__uint_as_float(v[6][0]) + __uint_as_float(v[7][0])));
            float sy = ((__uint_as_float(v[0][1]) + __uint_as_float(v[1][1])) + (__uint_as_float(v[2][1]) + __uint_as_float(v[3][1]))) +
                       ((__uint_as_float(v[4][1]) + __uint_as_float(v[5][1])) + (__uint_as_float(v[6][1]) + __uint_as_float(v[7][1])));
            sx += __shfl_xor_sync(0xffffffffu, sx, 16);
            sy += __shfl_xor_sync(0xffffffffu, sy, 16);
            const uint32_t ov = pack2(sx, sy);
            stg32(wps, ov);
            bar_arrive<BAR_E, CNT_E>();
            bar_arrive<BAR_E0, 64>();
            bar_arrive<BAR_T, CNT_T>();
            SCHED_FENCE();
            PROF(11);
            {
                const uint32_t b0 = __shfl_sync(0xffffffffu, ov, q), b1 = __shfl_sync(0xffffffffu, ov, 4 + q), b2 = __shfl_sync(0xffffffffu, ov, 8 + q), b3 = __shfl_sync(0xffffffffu, ov, 12 + q);
                stas128(qd0, b0, b1, b2, b3, qb0);
                stas128(qd0 + rank8, b0, b1, b2, b3, qb0 + rank8);
            }
            if (lane == 0) mbar_expect(barR, 2048);
            __syncwarp();
            wps = wp3 + ((s + 1) & 3) * 16384;
            wtl = wts + ((s + 1) & 3) * 16384;
        }
      } else {
        if (lane == 0) {
            const uint32_t ns = probe_near(g_SM + h * 65536, j), blk = h + 1;
            sts64(sb + SM_NEAR, ((ns ^ blk ^ (blk >> 1) ^ (blk >> 3)) & 1) * 4096, ns * 4096);
        }
        __syncwarp();
        g_role(sb, h, j, lane, dxf, budget);
      }
    }
    TL(4);
}

__device__ __forceinline__ void wg_n128_ss_tb(float* d, uint64_t da, uint64_t db, int sc) {
    asm volatile("{.reg .pred p; setp.ne.b32 p, %66, 0;\n\t"
                 "wgmma.mma_async.sync.aligned.m64n128k16.f32.bf16.bf16 {%0,%1,%2,%3,%4,%5,%6,%7,%8,%9,%10,%11,%12,%13,%14,%15,%16,%17,%18,%19,%20,%21,%22,%23,%24,%25,%26,%27,%28,%29,%30,%31,%32,%33,%34,%35,%36,%37,%38,%39,%40,%41,%42,%43,%44,%45,%46,%47,%48,%49,%50,%51,%52,%53,%54,%55,%56,%57,%58,%59,%60,%61,%62,%63}, %64, %65, p, 1, 1, 0, 1;}"
                 : "+f"(d[0]), "+f"(d[1]), "+f"(d[2]), "+f"(d[3]), "+f"(d[4]), "+f"(d[5]), "+f"(d[6]), "+f"(d[7]), "+f"(d[8]), "+f"(d[9]), "+f"(d[10]), "+f"(d[11]), "+f"(d[12]), "+f"(d[13]), "+f"(d[14]), "+f"(d[15]), "+f"(d[16]), "+f"(d[17]), "+f"(d[18]), "+f"(d[19]), "+f"(d[20]), "+f"(d[21]), "+f"(d[22]), "+f"(d[23]), "+f"(d[24]), "+f"(d[25]), "+f"(d[26]), "+f"(d[27]), "+f"(d[28]), "+f"(d[29]), "+f"(d[30]), "+f"(d[31]), "+f"(d[32]), "+f"(d[33]), "+f"(d[34]), "+f"(d[35]), "+f"(d[36]), "+f"(d[37]), "+f"(d[38]), "+f"(d[39]), "+f"(d[40]), "+f"(d[41]), "+f"(d[42]), "+f"(d[43]), "+f"(d[44]), "+f"(d[45]), "+f"(d[46]), "+f"(d[47]), "+f"(d[48]), "+f"(d[49]), "+f"(d[50]), "+f"(d[51]), "+f"(d[52]), "+f"(d[53]), "+f"(d[54]), "+f"(d[55]), "+f"(d[56]), "+f"(d[57]), "+f"(d[58]), "+f"(d[59]), "+f"(d[60]), "+f"(d[61]), "+f"(d[62]), "+f"(d[63])
                 : "l"(da), "l"(db), "r"(sc));
}
__device__ __forceinline__ void wg_n32_ss_tatb(float* d, uint64_t da, uint64_t db, int sc) {
    asm volatile("{.reg .pred p; setp.ne.b32 p, %18, 0;\n\t"
                 "wgmma.mma_async.sync.aligned.m64n32k16.f32.bf16.bf16 {%0,%1,%2,%3,%4,%5,%6,%7,%8,%9,%10,%11,%12,%13,%14,%15}, %16, %17, p, 1, 1, 1, 1;}"
                 : "+f"(d[0]), "+f"(d[1]), "+f"(d[2]), "+f"(d[3]), "+f"(d[4]), "+f"(d[5]), "+f"(d[6]), "+f"(d[7]), "+f"(d[8]), "+f"(d[9]), "+f"(d[10]), "+f"(d[11]), "+f"(d[12]), "+f"(d[13]), "+f"(d[14]), "+f"(d[15])
                 : "l"(da), "l"(db), "r"(sc));
}

__device__ float g_KVP[32 * 16 * 64 * 32];
__device__ __align__(16) bf16 g_KV[16 * 64 * 32];
__device__ __align__(128) bf16 g_O[S_TOK * DM];

constexpr int HS_X = 0;
constexpr int HS_W = 7 * 16384;
constexpr int HS_PHI = HS_W + 3 * 16384;
constexpr int HS_PH = HS_PHI + 32768;
constexpr int HS_V = HS_PH + 16384;
constexpr int HS_BAR = HS_V + 8192;
constexpr int HS_G = HS_BAR + 128;
constexpr int HELP_SMEM = 1024 + HS_G + 512;

__device__ __forceinline__ void helper_barrier(int tid) {
    bar_sync<1, 256>();
    if (tid == 0) {
        __threadfence();
        const unsigned target = (atomicAdd(&g_hbar, 1) / 16 + 1) * 16;
        for (int i = 0; i < (1 << 22); i++) {
            unsigned v;
            asm volatile("ld.acquire.gpu.global.u32 %0, [%1];" : "=r"(v) : "l"(&g_hbar) : "memory");
            if ((int)(v - target) >= 0) break;
            __nanosleep(200);
        }
    }
    bar_sync<1, 256>();
}

__device__ __forceinline__ void feature_map(const float (*pp)[4], int q, uint32_t* pos, uint32_t* neg) {
    const float L2E = 1.4426950408889634f;
#pragma unroll
    for (int hf = 0; hf < 2; hf++) {
        float v[8];
#pragma unroll
        for (int nt = 0; nt < 4; nt++) { v[2 * nt] = pp[nt][2 * hf] * L2E; v[2 * nt + 1] = pp[nt][2 * hf + 1] * L2E; }
        const bool ok = q < 2;
        float mx = fmaxf(fmaxf(fmaxf(v[0], v[1]), fmaxf(v[2], v[3])), fmaxf(v[4], v[5]));
        float mn = fminf(fminf(fminf(v[0], v[1]), fminf(v[2], v[3])), fminf(v[4], v[5]));
        if (ok) { mx = fmaxf(mx, fmaxf(v[6], v[7])); mn = fminf(mn, fminf(v[6], v[7])); }
        mx = fmaxf(mx, __shfl_xor_sync(0xffffffffu, mx, 1)); mn = fminf(mn, __shfl_xor_sync(0xffffffffu, mn, 1));
        mx = fmaxf(mx, __shfl_xor_sync(0xffffffffu, mx, 2)); mn = fminf(mn, __shfl_xor_sync(0xffffffffu, mn, 2));
        float ep[8], en[8], sp = 0.f, sn = 0.f;
#pragma unroll
        for (int i = 0; i < 8; i++) {
            ep[i] = (i < 6 || ok) ? ex2(v[i] - mx) : 0.f;
            en[i] = (i < 6 || ok) ? ex2(mn - v[i]) : 0.f;
            sp += ep[i]; sn += en[i];
        }
        sp += __shfl_xor_sync(0xffffffffu, sp, 1); sn += __shfl_xor_sync(0xffffffffu, sn, 1);
        sp += __shfl_xor_sync(0xffffffffu, sp, 2); sn += __shfl_xor_sync(0xffffffffu, sn, 2);
        const float ip = rcp(sp), in_ = rcp(sn);
#pragma unroll
        for (int nt = 0; nt < 4; nt++) {
            pos[2 * nt + hf] = pack2(ep[2 * nt] * ip, ep[2 * nt + 1] * ip);
            neg[2 * nt + hf] = pack2(en[2 * nt] * in_, en[2 * nt + 1] * in_);
        }
    }
}

__global__ void __launch_bounds__(384, 1)
k_help(const __grid_constant__ CUtensorMap tmXA, const __grid_constant__ CUtensorMap tmW, const __grid_constant__ CUtensorMap tmO,
       const __grid_constant__ CUtensorMap tmWo, const bf16* __restrict__ wphi, const bf16* __restrict__ gw, bf16* __restrict__ out,
       const bf16* __restrict__ wqkv, const bf16* __restrict__ woa) {
    extern __shared__ unsigned char smraw[];
    const uint32_t sb = (smem_u32(smraw) + 1023) & ~1023u;
    const int tid = threadIdx.x, warp = __shfl_sync(0xffffffffu, tid >> 5, 0), lane = tid & 31;
    const int g = lane >> 2, q = lane & 3;
    const int T0 = blockIdx.x * 128;
    constexpr int TLB = 15;
    TL(5);
    if (HDELAY) { const uint32_t t0 = gtime(); while (gtime() - t0 < HDELAY) __nanosleep(500); }
    const uint32_t barF = sb + HS_BAR, barE = barF + 24, barA = barF + 48, barGo = barF + 56;
    int budget = 1 << 28;
    if (tid == 0) {
        for (int i = 0; i < 3; i++) { mbar_init(barF + i * 8, 1); mbar_init(barE + i * 8, 2); }
        mbar_init(barA, 1);
        mbar_init(barGo, 1);
        asm volatile("fence.mbarrier_init.release.cluster;" ::: "memory");
    }
    __syncthreads();
    if (warp >= 8) {
        asm volatile("setmaxnreg.dec.sync.aligned.u32 40;");
        if (warp == 9 && lane < 4) {
            const bf16* src = lane < 3 ? wqkv + (size_t)(blockIdx.x * 3 + lane) * 12544 : woa + (size_t)blockIdx.x * 12544;
            asm volatile("cp.async.bulk.prefetch.L2.global [%0], %1;" ::"l"(src), "r"(25088) : "memory");
        }
        if (warp == 8 && lane == 0) {
            mbar_expect(barA, 7 * 16384);
            for (int i = 0; i < 28; i++) tma2d(sb + HS_X + (i >> 2) * 16384 + (i & 3) * 4096, &tmXA, (i >> 2) * 64, (i & 3) * 512 + blockIdx.x * 32, barA);
            for (int it = 0; it < (HEXP == 1 ? 0 : 16 * 7); it++) {
                const int ps = it / 7, kb = it % 7, st = it % 3;
                if (it == 12 * 7) {
                    for (int i = 0; i < 64 && !mbar_try(barGo, 0); i++) mbar_wait(barGo, 0, budget);
                    mbar_expect(barA, 7 * 16384);
                    for (int k2 = 0; k2 < 7; k2++) { tma2d(sb + HS_X + k2 * 16384, &tmO, k2 * 64, T0, barA); if (HTHROT) __nanosleep(400); }
                }
                if (it >= 3) { for (int i = 0; i < 64 && !mbar_try(barE + st * 8, ((it / 3) - 1) & 1); i++) mbar_wait(barE + st * 8, ((it / 3) - 1) & 1, budget); }
                mbar_expect(barF + st * 8, 16384);
                for (int u = 0; u < 4; u++) {
                    if (ps < 12) {
                        const int col = ps < 8 ? (1 + (ps & 1)) * DM + ((ps >> 1) * 4 + u) * 28 : ((ps - 8) * 4 + u) * 28;
                        tma2d(sb + HS_W + st * 16384 + u * 4096, &tmW, col - (u & 1) * 4, kb * 64, barF + st * 8);
                    } else {
                        tma2d(sb + HS_W + st * 16384 + u * 4096, &tmWo, (ps - 12) * 128 + u * 32, kb * 64, barF + st * 8);
                    }
                }
            }
        }
    } else {
        asm volatile("setmaxnreg.inc.sync.aligned.u32 232;");
        const int wg = warp >> 2, w = warp & 3;
        for (int half = 0; half < 2; half++) {
            for (int i = tid; i < 784; i += 256) {
                const uint4 v = ((const uint4*)wphi)[half * 784 + i];
                sts128(sb + HS_PH + i * 16, v.x, v.y, v.z, v.w);
            }
            bar_sync<1, 256>();
            const unsigned short* raw = (const unsigned short*)(smraw + (sb - smem_u32(smraw)) + HS_PH);
            for (int i = tid; i < 8 * 8 * 32; i += 256) {
                const int l = i & 31, nt = (i >> 5) & 3, ks = (i >> 7) & 1, hh = i >> 8, f = nt * 8 + (l >> 2);
                uint32_t r[2];
#pragma unroll
                for (int e = 0; e < 2; e++) {
                    const int d = ks * 16 + e * 8 + (l & 3) * 2 - (hh & 1) * 4;
                    const bool ok = d >= 0 && d < 28 && f < 28;
                    const uint32_t lo = ok ? raw[hh * 784 + d * 28 + f] : 0u, hi = ok ? raw[hh * 784 + (d + 1) * 28 + f] : 0u;
                    r[e] = lo | (hi << 16);
                }
                sts64(sb + HS_PHI + half * 16384 + i * 8, r[0], r[1]);
            }
            bar_sync<1, 256>();
        }
        mbar_wait(barA, 0, budget);
        {
            const int row = tid >> 1;
            float a = 0.f;
#pragma unroll 7
            for (int c = (tid & 1); c < 56; c += 2) {
                uint32_t v[4];
                lds128(v, sb + HS_X + (c >> 3) * 16384 + row * 128 + (((c & 7) ^ (row & 7)) << 4));
                const uint4 gq = *(const uint4*)(gw + c * 8);
                a += bf_lo(v[0]) * bf_lo(gq.x) + bf_hi(v[0]) * bf_hi(gq.x) + bf_lo(v[1]) * bf_lo(gq.y) + bf_hi(v[1]) * bf_hi(gq.y);
                a += bf_lo(v[2]) * bf_lo(gq.z) + bf_hi(v[2]) * bf_hi(gq.z) + bf_lo(v[3]) * bf_lo(gq.w) + bf_hi(v[3]) * bf_hi(gq.w);
            }
            a += __shfl_xor_sync(0xffffffffu, a, 1);
            if ((tid & 1) == 0) sts32(sb + HS_G + row * 4, __float_as_uint(1.f / (1.f + __expf(-a))));
        }
        bar_sync<1, 256>();
        TL(6);
        int it = 0;
        auto gemm = [&](float* acc) {
#pragma unroll 1
            for (int kb = 0; kb < (HEXP == 1 ? 0 : 7); kb++, it++) {
                const int st = it % 3;
                mbar_wait(barF + st * 8, (it / 3) & 1, budget);
                const uint64_t da = desc_sw128(sb + HS_X + kb * 16384 + wg * 8192);
                const uint64_t db = (uint64_t)(((sb + HS_W + st * 16384) & 0x3FFFF) >> 4) | ((uint64_t)256 << 16) | ((uint64_t)32 << 32) | ((uint64_t)2 << 62);
                WG_FENCE();
#pragma unroll
                for (int k = 0; k < 4; k++) wg_n128_ss_tb(acc, da + k * 2, db + k * 64, kb + k > 0);
                WG_COMMIT();
                WG_WAIT0();
                if ((tid & 127) == 0) mbar_arrive(barE + st * 8);
            }
        };
        auto project = [&](const float* acc, int hh, float (*pp)[4]) {
#pragma unroll
            for (int ks = 0; ks < 2; ks++) {
                const uint32_t a0 = pack2(acc[8 * ks], acc[8 * ks + 1]), a1 = pack2(acc[8 * ks + 2], acc[8 * ks + 3]);
                const uint32_t a2 = pack2(acc[8 * ks + 4], acc[8 * ks + 5]), a3 = pack2(acc[8 * ks + 6], acc[8 * ks + 7]);
#pragma unroll
                for (int nt = 0; nt < 4; nt++) {
                    uint32_t b[2];
                    lds64(b, sb + HS_PHI + ((hh * 2 + ks) * 4 + nt) * 256 + lane * 8);
                    if (ks == 0) mma16z(pp[nt], a0, a1, a2, a3, b[0], b[1]); else mma16(pp[nt], a0, a1, a2, a3, b[0], b[1]);
                }
            }
        };
        const int srow = w * 16 + (lane & 7) + 8 * ((lane >> 3) & 1);
#pragma unroll 1
        for (int G = 0; G < (HEXP == 1 ? 0 : 4); G++) {
            float ka[64], va[64];
            gemm(ka);
            if (G == 1) TL(13);
            gemm(va);
            if (G == 1) TL(14);
            if (G == 2) TL(15);
#pragma unroll
            for (int u = 0; u < 4; u++) {
                const int hh = G * 4 + u;
                float pp[4][4];
                project(&ka[16 * u], hh, pp);
                uint32_t pos[8], neg[8];
                feature_map(pp, q, pos, neg);
                const uint32_t ph = sb + HS_PH + wg * 8192 + srow * 128, vv = sb + HS_V + wg * 4096 + srow * 64;
#pragma unroll
                for (int c2 = 0; c2 < 2; c2++) {
                    stsm4(ph + (((2 * c2 + (lane >> 4)) ^ (srow & 7)) << 4), pos[4 * c2], pos[4 * c2 + 1], pos[4 * c2 + 2], pos[4 * c2 + 3]);
                    stsm4(ph + (((4 + 2 * c2 + (lane >> 4)) ^ (srow & 7)) << 4), neg[4 * c2], neg[4 * c2 + 1], neg[4 * c2 + 2], neg[4 * c2 + 3]);
                }
                uint32_t vw[8];
#pragma unroll
                for (int i = 0; i < 8; i++) vw[i] = pack2(va[16 * u + 2 * i], va[16 * u + 2 * i + 1]);
                if (u & 1) { if (q < 2) vw[0] = vw[1] = (q == 0 ? 0x00003f80u : 0u); }
                else { if (q >= 2) vw[6] = vw[7] = (q == 2 ? 0x00003f80u : 0u); }
#pragma unroll
                for (int c2 = 0; c2 < 2; c2++)
                    stsm4(vv + (((2 * c2 + (lane >> 4)) ^ ((srow >> 1) & 3)) << 4), vw[4 * c2], vw[4 * c2 + 1], vw[4 * c2 + 2], vw[4 * c2 + 3]);
                asm volatile("fence.proxy.async.shared::cta;" ::: "memory");
                if (wg == 0) bar_sync<2, 128>(); else bar_sync<3, 128>();
                float kv[16];
                const uint64_t da = desc_sw128(sb + HS_PH + wg * 8192);
                const uint64_t db = (uint64_t)(((sb + HS_V + wg * 4096) & 0x3FFFF) >> 4) | ((uint64_t)256 << 16) | ((uint64_t)32 << 32) | ((uint64_t)2 << 62);
                WG_FENCE();
#pragma unroll
                for (int k = 0; k < 4; k++) wg_n32_ss_tatb(kv, da + k * 128, db + k * 64, k > 0);
                WG_COMMIT();
                WG_WAIT0();
                float* o = g_KVP + ((size_t)(hh * 32 + blockIdx.x * 2 + wg) * 64 + w * 16 + g) * 32 + 2 * q;
#pragma unroll
                for (int nt = 0; nt < 4; nt++) {
                    if (HEXP != 2 || kv[0] == 1.2345f) *(float2*)(o + nt * 8) = make_float2(kv[4 * nt], kv[4 * nt + 1]);
                    if (HEXP != 2 || kv[0] == 1.2345f) *(float2*)(o + 256 + nt * 8) = make_float2(kv[4 * nt + 2], kv[4 * nt + 3]);
                }
                if (wg == 0) bar_sync<2, 128>(); else bar_sync<3, 128>();
            }
        }
        TL(7);
        __threadfence();
        helper_barrier(tid);
        {
            const float4* src = (const float4*)(g_KVP + (size_t)blockIdx.x * 32 * 2048) + tid;
            float4 s0 = make_float4(0.f, 0.f, 0.f, 0.f), s1 = s0;
#pragma unroll 1
            for (int pt = 0; pt < 32; pt++) {
                const float4 a = __ldcg(src + pt * 512), c = __ldcg(src + pt * 512 + 256);
                s0.x += a.x; s0.y += a.y; s0.z += a.z; s0.w += a.w;
                s1.x += c.x; s1.y += c.y; s1.z += c.z; s1.w += c.w;
            }
            sts128(sb + HS_PH + tid * 16, __float_as_uint(s0.x), __float_as_uint(s0.y), __float_as_uint(s0.z), __float_as_uint(s0.w));
            sts128(sb + HS_PH + 4096 + tid * 16, __float_as_uint(s1.x), __float_as_uint(s1.y), __float_as_uint(s1.z), __float_as_uint(s1.w));
            bar_sync<1, 256>();
            for (int i = tid; i < 1024; i += 256) {
                const int e = i & 1, l = (i >> 1) & 31, nt = (i >> 6) & 3, ks = i >> 8;
                const int f = ks * 16 + e * 8 + (l & 3) * 2, d = nt * 8 + (l >> 2);
                ((uint32_t*)g_KV)[blockIdx.x * 1024 + i] = pack2(__uint_as_float(lds32(sb + HS_PH + (f * 32 + d) * 4)), __uint_as_float(lds32(sb + HS_PH + ((f + 1) * 32 + d) * 4)));
            }
        }
        __threadfence();
        helper_barrier(tid);
        TL(8);
#pragma unroll 1
        for (int G = 0; G < (HEXP == 1 ? 0 : 4); G++) {
            float qa[64];
            bar_sync<1, 256>();
#pragma unroll
            for (int i = 0; i < 4; i++) {
                const uint4 v = __ldcg((const uint4*)g_KV + G * 1024 + i * 256 + tid);
                sts128(sb + HS_PH + (i * 256 + tid) * 16, v.x, v.y, v.z, v.w);
            }
            bar_sync<1, 256>();
            gemm(qa);
#pragma unroll
            for (int u = 0; u < 4; u++) {
                const int hh = G * 4 + u;
                float pp[4][4];
                project(&qa[16 * u], hh, pp);
                uint32_t ft[16];
                feature_map(pp, q, &ft[0], &ft[8]);
                float nm[4][4];
#pragma unroll
                for (int ks = 0; ks < 4; ks++)
#pragma unroll
                    for (int nt = 0; nt < 4; nt++) {
                        uint32_t b[2];
                        lds64(b, sb + HS_PH + u * 4096 + (ks * 4 + nt) * 256 + lane * 8);
                        if (ks == 0) mma16z(nm[nt], ft[0], ft[1], ft[2], ft[3], b[0], b[1]);
                        else mma16(nm[nt], ft[4 * ks], ft[4 * ks + 1], ft[4 * ks + 2], ft[4 * ks + 3], b[0], b[1]);
                    }
                const float i0 = 1.f / (__shfl_sync(0xffffffffu, nm[(u & 1) ? 0 : 3][0], (lane & ~3) | ((u & 1) ? 0 : 2)) + 1e-6f);
                const float i1 = 1.f / (__shfl_sync(0xffffffffu, nm[(u & 1) ? 0 : 3][2], (lane & ~3) | ((u & 1) ? 0 : 2)) + 1e-6f);
                uint32_t* o = (uint32_t*)(g_O + (size_t)(T0 + wg * 64 + w * 16 + g) * DM + hh * 28 - (u & 1) * 4 + 2 * q);
#pragma unroll
                for (int nt = 0; nt < 4; nt++) {
                    if ((HEXP != 2 || i0 == 1.2345f) && ((u & 1) ? (nt > 0 || q >= 2) : (nt < 3 || q < 2))) {
                        o[nt * 4] = pack2(nm[nt][0] * i0, nm[nt][1] * i0);
                        o[nt * 4 + 8 * DM / 2] = pack2(nm[nt][2] * i1, nm[nt][3] * i1);
                    }
                }
            }
        }
        asm volatile("fence.proxy.async;" ::: "memory");
        __threadfence();
        bar_sync<1, 256>();
        if (tid == 0) mbar_arrive(barGo);
        TL(9);
        if (HEXP != 1) mbar_wait(barA, 1, budget);
        const int r0 = wg * 64 + w * 16 + g;
        const float g0 = __uint_as_float(lds32(sb + HS_G + r0 * 4)), g1 = __uint_as_float(lds32(sb + HS_G + (r0 + 8) * 4));
        uint32_t ga[112];
#pragma unroll
        for (int ps = 0; ps < 4; ps++) {
            float acc[64];
            gemm(acc);
#pragma unroll
            for (int nt = 0; nt < (ps < 3 ? 16 : 8); nt++) {
                ga[ps * 32 + 2 * nt] = pack2(acc[4 * nt] * g0, acc[4 * nt + 1] * g0);
                ga[ps * 32 + 2 * nt + 1] = pack2(acc[4 * nt + 2] * g1, acc[4 * nt + 3] * g1);
            }
        }
        TL(10);
        bar_sync<1, 256>();
#pragma unroll
        for (int nt = 0; nt < 56; nt++) {
            sts32(sb + HS_X + r0 * 912 + nt * 16 + q * 4, ga[2 * nt]);
            sts32(sb + HS_X + (r0 + 8) * 912 + nt * 16 + q * 4, ga[2 * nt + 1]);
        }
        bar_sync<1, 256>();
        int tries = 1 << 16;
        const uint32_t par = (ldg32(&g_hbar) / 32) & 1;
#pragma unroll 1
        for (int rb = 0; rb < 4; rb++) {
            const int row = rb * 32 + warp * 4;
            const int tok = rb * 512 + blockIdx.x * 32 + warp * 4;
            const float* bp = g_B + (size_t)tok * DM + lane * 4;
            uint32_t v[14][4];
            if (HTHROT && rb < 3) __nanosleep(300 + 100 * warp);
            while (((ldg32(g_B + (size_t)(tok + 3) * DM + DM - 1) ^ par) & 1) && --tries > 0) { if (blockIdx.x < 13) __nanosleep(300); }
            if (rb == 3) TL(18);
            while (true) {
                uint32_t m = 0;
#pragma unroll
                for (int i = 0; i < 14; i++) ldg128(v[i], bp + i * 128);
#pragma unroll
                for (int i = 0; i < 14; i++) m |= (v[i][0] ^ par) | (v[i][1] ^ par) | (v[i][2] ^ par) | (v[i][3] ^ par);
                if (!__any_sync(0xffffffffu, m & 1) || --tries <= 0) break;
            }
            if (rb == 3) TL(19);
#pragma unroll
            for (int i = 0; i < 14; i++) {
                const int e = i * 32 + lane, rr = e / 112, cc = e - rr * 112;
                uint32_t a[2];
                lds64(a, sb + HS_X + (row + rr) * 912 + cc * 8);
                const float hg = 1.f - __uint_as_float(lds32(sb + HS_G + (row + rr) * 4));
                uint2 o;
                o.x = pack2(fmaf(hg, __uint_as_float(v[i][0]), bf_lo(a[0])), fmaf(hg, __uint_as_float(v[i][1]), bf_hi(a[0])));
                o.y = pack2(fmaf(hg, __uint_as_float(v[i][2]), bf_lo(a[1])), fmaf(hg, __uint_as_float(v[i][3]), bf_hi(a[1])));
                *(uint2*)(out + (size_t)tok * DM + e * 4) = o;
            }
        }
        TL(11);
        asm volatile("griddepcontrol.wait;" ::: "memory");
        TL(12);
    }
}

typedef CUresult (*EncodeFn)(CUtensorMap*, CUtensorMapDataType, cuuint32_t, void*, const cuuint64_t*, const cuuint64_t*,
                             const cuuint32_t*, const cuuint32_t*, CUtensorMapInterleave, CUtensorMapSwizzle,
                             CUtensorMapL2promotion, CUtensorMapFloatOOBfill);

static void make_map(EncodeFn enc, CUtensorMap* tm, const void* p, uint64_t cols, uint64_t rows, uint32_t bc, uint32_t br,
                     CUtensorMapSwizzle sw = CU_TENSOR_MAP_SWIZZLE_128B) {
    cuuint64_t dims[2] = {cols, rows};
    cuuint64_t strides[1] = {cols * 2};
    cuuint32_t box[2] = {bc, br};
    cuuint32_t es[2] = {1, 1};
    enc(tm, CU_TENSOR_MAP_DATA_TYPE_BFLOAT16, 2, (void*)p, dims, strides, box, es, CU_TENSOR_MAP_INTERLEAVE_NONE,
        sw, CU_TENSOR_MAP_L2_PROMOTION_L2_256B, CU_TENSOR_MAP_FLOAT_OOB_FILL_NONE);
}

#define P_D1 800
#define P_D3 800
int g_d1 = P_D1, g_d3 = P_D3, g_dx = 448, g_thr = 64, g_extra = 1256, g_dxf = 450, g_dpv = 480, g_dtx = 800, g_hold = 3;

extern "C" void kernel_launch(void* const* d_in, const int* in_sizes, int n_in, void* d_out, int out_size) {
    const bf16* x = (const bf16*)d_in[0];
    const bf16* wqkv = (const bf16*)d_in[1];
    const bf16* wphi = (const bf16*)d_in[2];
    const bf16* wo_a = (const bf16*)d_in[3];
    const bf16* mem0 = (const bf16*)d_in[5];
    const bf16* gw = (const bf16*)d_in[11];
    bf16* out = (bf16*)d_out;

    static EncodeFn enc = nullptr;
    if (!enc) {
        cudaDriverEntryPointQueryResult qr;
        cudaGetDriverEntryPoint("cuTensorMapEncodeTiled", (void**)&enc, cudaEnableDefault, &qr);
        cudaFuncSetAttribute(k_main, cudaFuncAttributeMaxDynamicSharedMemorySize, MAIN_SMEM);
        cudaFuncSetAttribute(k_main, cudaFuncAttributeNonPortableClusterSizeAllowed, 1);
        cudaFuncSetAttribute(k_help, cudaFuncAttributeMaxDynamicSharedMemorySize, HELP_SMEM);
    }
    CUtensorMap tmWq, tmWk, tmWv, tmWo, tmX;
    make_map(enc, &tmWq, d_in[6], 4096, 448, 64, 64);
    make_map(enc, &tmWk, d_in[7], 4096, 448, 64, 64);
    make_map(enc, &tmWv, d_in[8], 4096, 448, 64, 64);
    make_map(enc, &tmWo, d_in[9], 448, 4096, 64, 64);
    make_map(enc, &tmX, x, 448, 2048, 64, 32);

    cudaStream_t st = cudaStreamPerThread;

    cudaLaunchConfig_t cfg = {};
    cfg.gridDim = dim3(112);
    cfg.blockDim = dim3(384);
    cfg.dynamicSmemBytes = MAIN_SMEM;
    cfg.stream = st;
    cudaLaunchAttribute at[1];
    at[0].id = cudaLaunchAttributeClusterDimension;
    at[0].val.clusterDim.x = 16; at[0].val.clusterDim.y = 1; at[0].val.clusterDim.z = 1;
    cfg.attrs = at; cfg.numAttrs = 1;
    cudaLaunchKernelEx(&cfg, k_main, tmX, tmWq, tmWk, tmWv, tmWo, x, mem0, (const bf16*)d_in[6], (const bf16*)d_in[7], (const bf16*)d_in[8], (const bf16*)d_in[9], g_d1, g_d3, g_dx, g_thr, g_extra, g_dxf, g_dpv, g_dtx, g_hold, 0u);

    CUtensorMap tmXA, tmW, tmO, tmWoA;
    void* optr;
    cudaGetSymbolAddress(&optr, g_O);
    make_map(enc, &tmXA, x, 448, 2048, 64, 32);
    make_map(enc, &tmW, wqkv, 1344, 448, 32, 64, CU_TENSOR_MAP_SWIZZLE_64B);
    make_map(enc, &tmO, optr, 448, 2048, 64, 128);
    make_map(enc, &tmWoA, wo_a, 448, 448, 32, 64, CU_TENSOR_MAP_SWIZZLE_64B);
    cudaLaunchConfig_t hc = {};
    hc.gridDim = dim3(16);
    hc.blockDim = dim3(384);
    hc.dynamicSmemBytes = HELP_SMEM;
    hc.stream = st;
    cudaLaunchAttribute ha[1];
    ha[0].id = cudaLaunchAttributeProgrammaticStreamSerialization;
    ha[0].val.programmaticStreamSerializationAllowed = 1;
    hc.attrs = ha; hc.numAttrs = 1;
    cudaLaunchKernelEx(&hc, k_help, tmXA, tmW, tmO, tmWoA, wphi, gw, out, wqkv, wo_a);
}
```
